```python
import torch

def _softmax(x, axis=-1):
    return torch.softmax(x, dim=axis)
def _gelu(x):
    return torch.nn.functional.gelu(x, approximate="tanh")
def _silu(x):
    return torch.nn.functional.silu(x)
def _sigmoid(x):
    return torch.sigmoid(x)
def _layernorm(x, axis=-1, eps=1e-5):
    m = x.mean(dim=axis, keepdim=True)
    v = x.var(dim=axis, keepdim=True, unbiased=False)
    return (x - m) / torch.sqrt(v + eps)
def _scatter_add(tgt, idx, src, axis=0):
    return tgt.clone().index_add_(axis, idx, src)
def _segment_sum(src, seg, n):
    out = torch.zeros((n,) + src.shape[1:], dtype=src.dtype)
    return out.index_add_(0, seg, src)
def _pad(x, pw):
    flat = tuple(v for pair in reversed(pw) for v in pair)
    return torch.nn.functional.pad(x, flat)

kernel_name = 'concat_heads__softmax_full_mha__linear_attn_block__prompt'

def setup_inputs():

    _w = (lambda a: (lambda t: t.to(torch.bfloat16) if t.is_floating_point() else t)(torch.as_tensor(a)))
    def _A_setup():
        B, S, D = 1, 2048, 448
        return {
            "x": _w((lambda *s: torch.randn(*s, dtype=torch.bfloat16) * 0.2)(B, S, D)),
            "wqkv": _w((lambda *s: torch.randn(*s, dtype=torch.bfloat16) * 0.2)(D, 3 * D)),
            "wo": _w((lambda *s: torch.randn(*s, dtype=torch.bfloat16) * 0.05)(D, D)),
        }
    _A_in = _A_setup()

    def _B_setup():
        B, S, D = 1, 2048, 448
        return {
            "x": _w((lambda *s: torch.randn(*s, dtype=torch.bfloat16) * 0.05)(B, S, D)),
            "wqkv": _w((lambda *s: torch.randn(*s, dtype=torch.bfloat16) * 1.6)(D, 3 * D)),
            "wo": _w((lambda *s: torch.randn(*s, dtype=torch.bfloat16) * 0.05)(D, D)),
        }
    _B_in = _B_setup()

    return {
        "A_x": _A_in["x"],
        "A_wqkv": _A_in["wqkv"],
        "A_wo": _A_in["wo"],
        "B_x": _B_in["x"],
        "B_wqkv": _B_in["wqkv"],
        "B_wo": _B_in["wo"],
    }

def reference(A_x, A_wqkv, A_wo, B_x, B_wqkv, B_wo):
    def _A_ref(x, wqkv, wo):
        B, S, D = x.shape
        H = 16; Dh = D // H
        qkv = (lambda x, *d: x.permute(*d))((x @ wqkv).reshape(B, S, 3, H, Dh), 2, 0, 3, 1, 4)
        q, k, v = qkv[0], qkv[1], qkv[2]
        scale = Dh ** -0.5
        scores = torch.einsum("bhqd,bhkd->bhqk", q, k) * scale
        p = _softmax(scores, axis=-1)
        o = torch.einsum("bhqk,bhkd->bhqd", p, v)
        return (lambda x, *d: x.permute(*d))(o, 0, 2, 1, 3).reshape(B, S, D) @ wo

    def _B_ref(x, wqkv, wo):
        B, S, D = x.shape
        H = 16; Dh = D // H
        qkv = (lambda x, *d: x.permute(*d))((x @ wqkv).reshape(B, S, 3, H, Dh), 2, 0, 3, 1, 4)
        q, k, v = qkv[0], qkv[1], qkv[2]
        phi = lambda t: torch.where(t > 0, t + 1, torch.exp(t)) + 1e-6
        pq, pk = phi(q), phi(k)
        kv = torch.einsum("bhsd,bhse->bhde", pk, v)
        z = torch.einsum("bhsd->bhd", pk)
        num = torch.einsum("bhqd,bhde->bhqe", pq, kv)
        den = torch.einsum("bhqd,bhd->bhq", pq, z)[..., None] + 1e-6
        o = num / den
        return (lambda x, *d: x.permute(*d))(o, 0, 2, 1, 3).reshape(B, S, D) @ wo

    a = _A_ref(A_x, A_wqkv, A_wo)
    b = _B_ref(B_x, B_wqkv, B_wo)
    return torch.concatenate([a, b], axis=-1)
```

```cpp
#include <cuda_runtime.h>
#include <cuda.h>
#include <cuda_bf16.h>
#include <stdint.h>

namespace {

constexpr int NTHREADS = 640;
constexpr int NCTA = 132;

constexpr uint32_t HEAD_STRIDE = 16 * 24576;
__device__ __align__(1024) uint8_t gQKV[2][16 * HEAD_STRIDE];
__device__ __align__(1024) uint8_t gO[2][32 * 57344];
__device__ __align__(1024) float gPart[16 * 8 * 1024];
__device__ unsigned gCnt[96 * 32];
__device__ unsigned long long gKn[128];
__device__ unsigned gEpoch[NCTA];
constexpr int C_A = 0, C_BK = 8, C_BQ = 16, C_OB = 24, C_KV = 32, C_OA = 48;

#define STAMP(i) do {} while (0)

constexpr uint32_t STAGE = 40960;
constexpr uint32_t S_RING = 0;
constexpr uint32_t S_WOB = 98304;
constexpr uint32_t S_WOA = 155648;
constexpr uint32_t S_PKV = S_WOA;
constexpr uint32_t S_PQ = S_WOA + 32768;
constexpr uint32_t S_KVM = S_WOA + 49152;
constexpr uint32_t S_Q = 212992;
constexpr uint32_t S_BAR = 229376;
constexpr uint32_t S_MISC = S_BAR + 2048;
constexpr uint32_t SMEM_BYTES = S_MISC + 64;
constexpr int B_GF = 0, B_GE = 28, B_KF = 56, B_KE = 72, B_OF = 88, B_OE = 116, B_QF = 132, B_PKV = 133, B_PQ = 134,
              B_PART = 135, B_KVM = 136, B_XFREE = 137, B_WOB = 138, B_WOA = 139, B_GUARD = 140, B_SG = 141  ,
              B_SKV = 145, B_SOB = 146, B_END = 147;

constexpr uint32_t EMU_MASK = 0xB5B5;
constexpr int T_KVP = 3, T_OB = 9;
constexpr float GUARD = 47.0f * 47.0f;

struct Params { CUtensorMap x[2], w[2], wo[2]; };

__device__ __forceinline__ void wg_fence() { asm volatile("wgmma.fence.sync.aligned;" ::: "memory"); }
__device__ __forceinline__ void wg_commit() { asm volatile("wgmma.commit_group.sync.aligned;" ::: "memory"); }
template <int N> __device__ __forceinline__ void wg_wait() { asm volatile("wgmma.wait_group.sync.aligned %0;" ::"n"(N) : "memory"); }
template <int M, int N> __device__ __forceinline__ void pin(float (&d)[N]) {
#pragma unroll
  for (int i = 0; i < M; i++) asm volatile("" : "+f"(d[i])::"memory");
}
template <int M, int N> __device__ __forceinline__ void pin(uint32_t (&d)[N]) {
#pragma unroll
  for (int i = 0; i < M; i++) asm volatile("" : "+r"(d[i])::"memory");
}
template<uint32_t HA, uint32_t HB, int NN> __device__ __forceinline__ void wg128_ss(float (&d)[NN], uint32_t al, uint32_t bl) {
  asm volatile("{\n.reg .pred p;\n.reg .b64 da, db;\nsetp.ne.b32 p, 1, 0;\nmov.b64 da, {%64, %66};\nmov.b64 db, {%65, %67};\n"
    "wgmma.mma_async.sync.aligned.m64n128k16.f32.bf16.bf16 {%0,%1,%2,%3,%4,%5,%6,%7,%8,%9,%10,%11,%12,%13,%14,%15,%16,%17,%18,%19,%20,%21,%22,%23,%24,%25,%26,%27,%28,%29,%30,%31,%32,%33,%34,%35,%36,%37,%38,%39,%40,%41,%42,%43,%44,%45,%46,%47,%48,%49,%50,%51,%52,%53,%54,%55,%56,%57,%58,%59,%60,%61,%62,%63}, da, db, p, 1, 1, 0, 0;\n}\n"
    : "+f"(d[0]),"+f"(d[1]),"+f"(d[2]),"+f"(d[3]),"+f"(d[4]),"+f"(d[5]),"+f"(d[6]),"+f"(d[7]),"+f"(d[8]),"+f"(d[9]),"+f"(d[10]),"+f"(d[11]),"+f"(d[12]),"+f"(d[13]),"+f"(d[14]),"+f"(d[15]),"+f"(d[16]),"+f"(d[17]),"+f"(d[18]),"+f"(d[19]),"+f"(d[20]),"+f"(d[21]),"+f"(d[22]),"+f"(d[23]),"+f"(d[24]),"+f"(d[25]),"+f"(d[26]),"+f"(d[27]),"+f"(d[28]),"+f"(d[29]),"+f"(d[30]),"+f"(d[31]),"+f"(d[32]),"+f"(d[33]),"+f"(d[34]),"+f"(d[35]),"+f"(d[36]),"+f"(d[37]),"+f"(d[38]),"+f"(d[39]),"+f"(d[40]),"+f"(d[41]),"+f"(d[42]),"+f"(d[43]),"+f"(d[44]),"+f"(d[45]),"+f"(d[46]),"+f"(d[47]),"+f"(d[48]),"+f"(d[49]),"+f"(d[50]),"+f"(d[51]),"+f"(d[52]),"+f"(d[53]),"+f"(d[54]),"+f"(d[55]),"+f"(d[56]),"+f"(d[57]),"+f"(d[58]),"+f"(d[59]),"+f"(d[60]),"+f"(d[61]),"+f"(d[62]),"+f"(d[63])
    : "r"(al), "r"(bl), "n"(HA), "n"(HB));
}
template<uint32_t HA, uint32_t HB, int NN> __device__ __forceinline__ void wg128_ss_z(float (&d)[NN], uint32_t al, uint32_t bl) {
  asm volatile("{\n.reg .pred p;\n.reg .b64 da, db;\nsetp.ne.b32 p, 0, 0;\nmov.b64 da, {%64, %66};\nmov.b64 db, {%65, %67};\n"
    "wgmma.mma_async.sync.aligned.m64n128k16.f32.bf16.bf16 {%0,%1,%2,%3,%4,%5,%6,%7,%8,%9,%10,%11,%12,%13,%14,%15,%16,%17,%18,%19,%20,%21,%22,%23,%24,%25,%26,%27,%28,%29,%30,%31,%32,%33,%34,%35,%36,%37,%38,%39,%40,%41,%42,%43,%44,%45,%46,%47,%48,%49,%50,%51,%52,%53,%54,%55,%56,%57,%58,%59,%60,%61,%62,%63}, da, db, p, 1, 1, 0, 0;\n}\n"
    : "=f"(d[0]),"=f"(d[1]),"=f"(d[2]),"=f"(d[3]),"=f"(d[4]),"=f"(d[5]),"=f"(d[6]),"=f"(d[7]),"=f"(d[8]),"=f"(d[9]),"=f"(d[10]),"=f"(d[11]),"=f"(d[12]),"=f"(d[13]),"=f"(d[14]),"=f"(d[15]),"=f"(d[16]),"=f"(d[17]),"=f"(d[18]),"=f"(d[19]),"=f"(d[20]),"=f"(d[21]),"=f"(d[22]),"=f"(d[23]),"=f"(d[24]),"=f"(d[25]),"=f"(d[26]),"=f"(d[27]),"=f"(d[28]),"=f"(d[29]),"=f"(d[30]),"=f"(d[31]),"=f"(d[32]),"=f"(d[33]),"=f"(d[34]),"=f"(d[35]),"=f"(d[36]),"=f"(d[37]),"=f"(d[38]),"=f"(d[39]),"=f"(d[40]),"=f"(d[41]),"=f"(d[42]),"=f"(d[43]),"=f"(d[44]),"=f"(d[45]),"=f"(d[46]),"=f"(d[47]),"=f"(d[48]),"=f"(d[49]),"=f"(d[50]),"=f"(d[51]),"=f"(d[52]),"=f"(d[53]),"=f"(d[54]),"=f"(d[55]),"=f"(d[56]),"=f"(d[57]),"=f"(d[58]),"=f"(d[59]),"=f"(d[60]),"=f"(d[61]),"=f"(d[62]),"=f"(d[63])
    : "r"(al), "r"(bl), "n"(HA), "n"(HB));
}
template<uint32_t HA, uint32_t HB, int NN> __device__ __forceinline__ void wg128_ss_tb(float (&d)[NN], uint32_t al, uint32_t bl) {
  asm volatile("{\n.reg .pred p;\n.reg .b64 da, db;\nsetp.ne.b32 p, 1, 0;\nmov.b64 da, {%64, %66};\nmov.b64 db, {%65, %67};\n"
    "wgmma.mma_async.sync.aligned.m64n128k16.f32.bf16.bf16 {%0,%1,%2,%3,%4,%5,%6,%7,%8,%9,%10,%11,%12,%13,%14,%15,%16,%17,%18,%19,%20,%21,%22,%23,%24,%25,%26,%27,%28,%29,%30,%31,%32,%33,%34,%35,%36,%37,%38,%39,%40,%41,%42,%43,%44,%45,%46,%47,%48,%49,%50,%51,%52,%53,%54,%55,%56,%57,%58,%59,%60,%61,%62,%63}, da, db, p, 1, 1, 0, 1;\n}\n"
    : "+f"(d[0]),"+f"(d[1]),"+f"(d[2]),"+f"(d[3]),"+f"(d[4]),"+f"(d[5]),"+f"(d[6]),"+f"(d[7]),"+f"(d[8]),"+f"(d[9]),"+f"(d[10]),"+f"(d[11]),"+f"(d[12]),"+f"(d[13]),"+f"(d[14]),"+f"(d[15]),"+f"(d[16]),"+f"(d[17]),"+f"(d[18]),"+f"(d[19]),"+f"(d[20]),"+f"(d[21]),"+f"(d[22]),"+f"(d[23]),"+f"(d[24]),"+f"(d[25]),"+f"(d[26]),"+f"(d[27]),"+f"(d[28]),"+f"(d[29]),"+f"(d[30]),"+f"(d[31]),"+f"(d[32]),"+f"(d[33]),"+f"(d[34]),"+f"(d[35]),"+f"(d[36]),"+f"(d[37]),"+f"(d[38]),"+f"(d[39]),"+f"(d[40]),"+f"(d[41]),"+f"(d[42]),"+f"(d[43]),"+f"(d[44]),"+f"(d[45]),"+f"(d[46]),"+f"(d[47]),"+f"(d[48]),"+f"(d[49]),"+f"(d[50]),"+f"(d[51]),"+f"(d[52]),"+f"(d[53]),"+f"(d[54]),"+f"(d[55]),"+f"(d[56]),"+f"(d[57]),"+f"(d[58]),"+f"(d[59]),"+f"(d[60]),"+f"(d[61]),"+f"(d[62]),"+f"(d[63])
    : "r"(al), "r"(bl), "n"(HA), "n"(HB));
}
template<uint32_t HB, int NN> __device__ __forceinline__ void wg32_rs_tb(float (&d)[NN], uint32_t a0, uint32_t a1, uint32_t a2, uint32_t a3, uint32_t bl) {
  asm volatile("{\n.reg .pred p;\n.reg .b64 db;\nsetp.ne.b32 p, 1, 0;\nmov.b64 db, {%20, %21};\n"
    "wgmma.mma_async.sync.aligned.m64n32k16.f32.bf16.bf16 {%0,%1,%2,%3,%4,%5,%6,%7,%8,%9,%10,%11,%12,%13,%14,%15}, {%16,%17,%18,%19}, db, p, 1, 1, 1;\n}\n"
    : "+f"(d[0]),"+f"(d[1]),"+f"(d[2]),"+f"(d[3]),"+f"(d[4]),"+f"(d[5]),"+f"(d[6]),"+f"(d[7]),"+f"(d[8]),"+f"(d[9]),"+f"(d[10]),"+f"(d[11]),"+f"(d[12]),"+f"(d[13]),"+f"(d[14]),"+f"(d[15])
    : "r"(a0), "r"(a1), "r"(a2), "r"(a3), "r"(bl), "n"(HB));
}
template<uint32_t HA, uint32_t HB, int NN> __device__ __forceinline__ void wg32_ss_tb(float (&d)[NN], uint32_t al, uint32_t bl) {
  asm volatile("{\n.reg .pred p;\n.reg .b64 da, db;\nsetp.ne.b32 p, 1, 0;\nmov.b64 da, {%16, %18};\nmov.b64 db, {%17, %19};\n"
    "wgmma.mma_async.sync.aligned.m64n32k16.f32.bf16.bf16 {%0,%1,%2,%3,%4,%5,%6,%7,%8,%9,%10,%11,%12,%13,%14,%15}, da, db, p, 1, 1, 0, 1;\n}\n"
    : "+f"(d[0]),"+f"(d[1]),"+f"(d[2]),"+f"(d[3]),"+f"(d[4]),"+f"(d[5]),"+f"(d[6]),"+f"(d[7]),"+f"(d[8]),"+f"(d[9]),"+f"(d[10]),"+f"(d[11]),"+f"(d[12]),"+f"(d[13]),"+f"(d[14]),"+f"(d[15])
    : "r"(al), "r"(bl), "n"(HA), "n"(HB));
}
template<uint32_t HA, uint32_t HB, int NN> __device__ __forceinline__ void wg32_ss_tb_z(float (&d)[NN], uint32_t al, uint32_t bl) {
  asm volatile("{\n.reg .pred p;\n.reg .b64 da, db;\nsetp.ne.b32 p, 0, 0;\nmov.b64 da, {%16, %18};\nmov.b64 db, {%17, %19};\n"
    "wgmma.mma_async.sync.aligned.m64n32k16.f32.bf16.bf16 {%0,%1,%2,%3,%4,%5,%6,%7,%8,%9,%10,%11,%12,%13,%14,%15}, da, db, p, 1, 1, 0, 1;\n}\n"
    : "=f"(d[0]),"=f"(d[1]),"=f"(d[2]),"=f"(d[3]),"=f"(d[4]),"=f"(d[5]),"=f"(d[6]),"=f"(d[7]),"=f"(d[8]),"=f"(d[9]),"=f"(d[10]),"=f"(d[11]),"=f"(d[12]),"=f"(d[13]),"=f"(d[14]),"=f"(d[15])
    : "r"(al), "r"(bl), "n"(HA), "n"(HB));
}
template<uint32_t HA, uint32_t HB, int NN> __device__ __forceinline__ void wg32_ss_ta_tb(float (&d)[NN], uint32_t al, uint32_t bl) {
  asm volatile("{\n.reg .pred p;\n.reg .b64 da, db;\nsetp.ne.b32 p, 1, 0;\nmov.b64 da, {%16, %18};\nmov.b64 db, {%17, %19};\n"
    "wgmma.mma_async.sync.aligned.m64n32k16.f32.bf16.bf16 {%0,%1,%2,%3,%4,%5,%6,%7,%8,%9,%10,%11,%12,%13,%14,%15}, da, db, p, 1, 1, 1, 1;\n}\n"
    : "+f"(d[0]),"+f"(d[1]),"+f"(d[2]),"+f"(d[3]),"+f"(d[4]),"+f"(d[5]),"+f"(d[6]),"+f"(d[7]),"+f"(d[8]),"+f"(d[9]),"+f"(d[10]),"+f"(d[11]),"+f"(d[12]),"+f"(d[13]),"+f"(d[14]),"+f"(d[15])
    : "r"(al), "r"(bl), "n"(HA), "n"(HB));
}
template<uint32_t HA, uint32_t HB, int NN> __device__ __forceinline__ void wg32_ss_ta_tb_z(float (&d)[NN], uint32_t al, uint32_t bl) {
  asm volatile("{\n.reg .pred p;\n.reg .b64 da, db;\nsetp.ne.b32 p, 0, 0;\nmov.b64 da, {%16, %18};\nmov.b64 db, {%17, %19};\n"
    "wgmma.mma_async.sync.aligned.m64n32k16.f32.bf16.bf16 {%0,%1,%2,%3,%4,%5,%6,%7,%8,%9,%10,%11,%12,%13,%14,%15}, da, db, p, 1, 1, 1, 1;\n}\n"
    : "=f"(d[0]),"=f"(d[1]),"=f"(d[2]),"=f"(d[3]),"=f"(d[4]),"=f"(d[5]),"=f"(d[6]),"=f"(d[7]),"=f"(d[8]),"=f"(d[9]),"=f"(d[10]),"=f"(d[11]),"=f"(d[12]),"=f"(d[13]),"=f"(d[14]),"=f"(d[15])
    : "r"(al), "r"(bl), "n"(HA), "n"(HB));
}
template<uint32_t HA, uint32_t HB, int NN> __device__ __forceinline__ void wg56_ss_tb(float (&d)[NN], uint32_t al, uint32_t bl) {
  asm volatile("{\n.reg .pred p;\n.reg .b64 da, db;\nsetp.ne.b32 p, 1, 0;\nmov.b64 da, {%28, %30};\nmov.b64 db, {%29, %31};\n"
    "wgmma.mma_async.sync.aligned.m64n56k16.f32.bf16.bf16 {%0,%1,%2,%3,%4,%5,%6,%7,%8,%9,%10,%11,%12,%13,%14,%15,%16,%17,%18,%19,%20,%21,%22,%23,%24,%25,%26,%27}, da, db, p, 1, 1, 0, 1;\n}\n"
    : "+f"(d[0]),"+f"(d[1]),"+f"(d[2]),"+f"(d[3]),"+f"(d[4]),"+f"(d[5]),"+f"(d[6]),"+f"(d[7]),"+f"(d[8]),"+f"(d[9]),"+f"(d[10]),"+f"(d[11]),"+f"(d[12]),"+f"(d[13]),"+f"(d[14]),"+f"(d[15]),"+f"(d[16]),"+f"(d[17]),"+f"(d[18]),"+f"(d[19]),"+f"(d[20]),"+f"(d[21]),"+f"(d[22]),"+f"(d[23]),"+f"(d[24]),"+f"(d[25]),"+f"(d[26]),"+f"(d[27])
    : "r"(al), "r"(bl), "n"(HA), "n"(HB));
}
template<uint32_t HA, uint32_t HB, int NN> __device__ __forceinline__ void wg64_ss_tb(float (&d)[NN], uint32_t al, uint32_t bl) {
  asm volatile("{\n.reg .pred p;\n.reg .b64 da, db;\nsetp.ne.b32 p, 1, 0;\nmov.b64 da, {%32, %34};\nmov.b64 db, {%33, %35};\n"
    "wgmma.mma_async.sync.aligned.m64n64k16.f32.bf16.bf16 {%0,%1,%2,%3,%4,%5,%6,%7,%8,%9,%10,%11,%12,%13,%14,%15,%16,%17,%18,%19,%20,%21,%22,%23,%24,%25,%26,%27,%28,%29,%30,%31}, da, db, p, 1, 1, 0, 1;\n}\n"
    : "+f"(d[0]),"+f"(d[1]),"+f"(d[2]),"+f"(d[3]),"+f"(d[4]),"+f"(d[5]),"+f"(d[6]),"+f"(d[7]),"+f"(d[8]),"+f"(d[9]),"+f"(d[10]),"+f"(d[11]),"+f"(d[12]),"+f"(d[13]),"+f"(d[14]),"+f"(d[15]),"+f"(d[16]),"+f"(d[17]),"+f"(d[18]),"+f"(d[19]),"+f"(d[20]),"+f"(d[21]),"+f"(d[22]),"+f"(d[23]),"+f"(d[24]),"+f"(d[25]),"+f"(d[26]),"+f"(d[27]),"+f"(d[28]),"+f"(d[29]),"+f"(d[30]),"+f"(d[31])
    : "r"(al), "r"(bl), "n"(HA), "n"(HB));
}

__device__ __forceinline__ void mbar_init(uint32_t a, uint32_t c) { asm volatile("mbarrier.init.shared::cta.b64 [%0], %1;" ::"r"(a), "r"(c) : "memory"); }
__device__ __forceinline__ void mbar_expect(uint32_t a, uint32_t b) { asm volatile("mbarrier.arrive.expect_tx.shared::cta.b64 _, [%0], %1;" ::"r"(a), "r"(b) : "memory"); }
__device__ __forceinline__ void mbar_arrive(uint32_t a) { asm volatile("mbarrier.arrive.shared::cta.b64 _, [%0];" ::"r"(a) : "memory"); }
__device__ __forceinline__ void mbar_wait(uint32_t a) {
  asm volatile("{\n.reg .pred p;\n.reg .u32 n;\nmov.u32 n, 0;\nLW:\n"
               "mbarrier.try_wait.parity.shared::cta.b64 p, [%0], 0;\n@p bra LD;\n"
               "add.u32 n, n, 1;\nsetp.lt.u32 p, n, 0x400000;\n@p bra LW;\ntrap;\nLD:\n}\n" ::"r"(a) : "memory");
}
__device__ __forceinline__ void warp_arrive(uint32_t a) { __syncwarp(); if ((threadIdx.x & 31) == 0) mbar_arrive(a); }
__device__ __forceinline__ void tma2d(uint32_t dst, const CUtensorMap* m, int c0, int c1, uint32_t bar) {
  asm volatile("cp.async.bulk.tensor.2d.shared::cluster.global.mbarrier::complete_tx::bytes [%0], [%1, {%3, %4}], [%2];"
               ::"r"(dst), "l"(m), "r"(bar), "r"(c0), "r"(c1) : "memory");
}
__device__ __forceinline__ void bulk(uint32_t dst, const void* src, uint32_t bytes, uint32_t bar) {
  asm volatile("cp.async.bulk.shared::cluster.global.mbarrier::complete_tx::bytes [%0], [%1], %2, [%3];"
               ::"r"(dst), "l"(src), "r"(bytes), "r"(bar) : "memory");
}
__device__ __forceinline__ void signal(int c) { asm volatile("red.release.gpu.global.add.u32 [%0], 1;" ::"l"(&gCnt[c * 32]) : "memory"); }
__device__ __forceinline__ void poll(int c, unsigned target) {
  for (int n = 0;; n++) {
    unsigned v;
    asm volatile("ld.acquire.gpu.global.u32 %0, [%1];" : "=r"(v) : "l"(&gCnt[c * 32]) : "memory");
    if ((int)(v - target) >= 0) break;
    if (n > (1 << 22)) __trap();
  }
}
__device__ __forceinline__ void proxy_fence() { asm volatile("fence.proxy.async;" ::: "memory"); }
__device__ __forceinline__ float ex2(float x) { float y; asm("ex2.approx.ftz.f32 %0, %1;" : "=f"(y) : "f"(x)); return y; }
__device__ __forceinline__ uint32_t pack(float lo, float hi) { uint32_t y; asm("cvt.rn.bf16x2.f32 %0, %1, %2;" : "=r"(y) : "f"(hi), "f"(lo)); return y; }
__device__ __forceinline__ void stg(uint8_t* p, uint32_t v) { asm volatile("st.global.u32 [%0], %1;" ::"l"(p), "r"(v) : "memory"); }
__device__ __forceinline__ uint32_t lds(uint32_t a) { uint32_t v; asm volatile("ld.shared.u32 %0, [%1];" : "=r"(v) : "r"(a) : "memory"); return v; }
__device__ __forceinline__ float sq2(uint32_t v, float a) {
  float lo = __uint_as_float(v << 16), hi = __uint_as_float(v & 0xFFFF0000u);
  return fmaf(lo, lo, fmaf(hi, hi, a));
}
__device__ __forceinline__ uint32_t exp2_pair(float t0, float t1) {
  uint32_t w = __byte_perm(__float_as_uint(t0), __float_as_uint(t1), 0x6521);
  uint32_t m = w | 0x3F803F80u, g;
  asm("fma.rn.bf16x2 %0, %1, %1, %2;" : "=r"(g) : "r"(m), "r"(0x40014001u));
  return g + w - m;
}
__device__ __forceinline__ float phi(float t) { return (t > 0.f ? t + 1.f : ex2(t * 1.4426950408889634f)) + 1e-6f; }

constexpr uint32_t H_SW = (1024 >> 4) | (1u << 30);
constexpr uint32_t L_X = 1u << 16, L_W = (8192u >> 4) << 16;
constexpr uint32_t H_KM = 512 >> 4, L_KM = (128u >> 4) << 16;
constexpr uint32_t H_MN = 128 >> 4, L_MN = (512u >> 4) << 16;
constexpr uint32_t H_O = 1024 >> 4;

__device__ __forceinline__ void store_o(const float* o, float eps, uint8_t* base, int h, int lane) {
  const int src = (lane & 28) | ((h & 1) ? 0 : 2);
  const float r0 = __fdividef(1.f, __shfl_sync(~0u, o[12], src) + eps), r1 = __fdividef(1.f, __shfl_sync(~0u, o[14], src) + eps);
#pragma unroll
  for (int c = 0; c < 4; c++) {
    const int G = 7 * (h >> 1) + (c == 3 ? 3 : (h & 1) * 4 + c);
    uint8_t* p = base + (G >> 3) * 8192 + (G & 7) * 128;
    if (c < 3 || ((lane >> 1) & 1) == (h & 1)) {
      stg(p, pack(o[4 * c] * r0, o[4 * c + 1] * r0));
      stg(p + 1024, pack(o[4 * c + 2] * r1, o[4 * c + 3] * r1));
    }
  }
}

__device__ __forceinline__ void mma16816(float* d, uint32_t a0, uint32_t a1, uint32_t a2, uint32_t a3, uint32_t b0, uint32_t b1) {
  asm volatile("mma.sync.aligned.m16n8k16.row.col.f32.bf16.bf16.f32 {%0,%1,%2,%3}, {%4,%5,%6,%7}, {%8,%9}, {%0,%1,%2,%3};"
               : "+f"(d[0]), "+f"(d[1]), "+f"(d[2]), "+f"(d[3]) : "r"(a0), "r"(a1), "r"(a2), "r"(a3), "r"(b0), "r"(b1));
}
__device__ __forceinline__ void attn_safe(float* o, uint32_t sq, const uint8_t* kv, int h, int lane) {
  uint32_t q[8];
#pragma unroll
  for (int i = 0; i < 8; i++) q[i] = lds(sq + (i & 1) * 512 + (i >> 1) * 128);
  if (((lane >> 1) & 1) != (h & 1)) q[6] = q[7] = 0;
  float m0 = -INFINITY, m1 = -INFINITY;
#pragma unroll
  for (int i = 0; i < 16; i++) o[i] = 0.f;
#pragma unroll 1
  for (int it = 0; it < 128; it++) {
    const uint32_t* k = (const uint32_t*)(kv + (it >> 3) * 24576 + (it & 7) * 1024) + lane;
    uint32_t kb[8], vb[8];
#pragma unroll
    for (int i = 0; i < 8; i++) { kb[i] = __ldcg(k + i * 32); vb[i] = __ldcg(k + 2048 + i * 32); }
    float s[8];
#pragma unroll
    for (int b = 0; b < 2; b++) {
      s[4 * b] = s[4 * b + 1] = s[4 * b + 2] = s[4 * b + 3] = 0.f;
      mma16816(s + 4 * b, q[0], q[1], q[2], q[3], kb[4 * b], kb[4 * b + 1]);
      mma16816(s + 4 * b, q[4], q[5], q[6], q[7], kb[4 * b + 2], kb[4 * b + 3]);
      const float f = ((EMU_MASK >> ((it & 7) * 2 + b)) & 1) ? 0.5f : 1.f;
#pragma unroll
      for (int i = 0; i < 4; i++) s[4 * b + i] *= f;
    }
    float n0 = fmaxf(fmaxf(s[0], s[1]), fmaxf(s[4], s[5])), n1 = fmaxf(fmaxf(s[2], s[3]), fmaxf(s[6], s[7]));
    n0 = fmaxf(n0, __shfl_xor_sync(~0u, n0, 1)); n1 = fmaxf(n1, __shfl_xor_sync(~0u, n1, 1));
    n0 = fmaxf(n0, __shfl_xor_sync(~0u, n0, 2)); n1 = fmaxf(n1, __shfl_xor_sync(~0u, n1, 2));
    n0 = fmaxf(n0, m0); n1 = fmaxf(n1, m1);
    const float a0 = ex2(m0 - n0), a1 = ex2(m1 - n1);
    m0 = n0; m1 = n1;
    const uint32_t p0 = pack(ex2(s[0] - m0), ex2(s[1] - m0)), p1 = pack(ex2(s[2] - m1), ex2(s[3] - m1));
    const uint32_t p2 = pack(ex2(s[4] - m0), ex2(s[5] - m0)), p3 = pack(ex2(s[6] - m1), ex2(s[7] - m1));
#pragma unroll
    for (int c = 0; c < 4; c++) {
      o[4 * c] *= a0; o[4 * c + 1] *= a0; o[4 * c + 2] *= a1; o[4 * c + 3] *= a1;
      uint32_t b0, b1;
      asm volatile("movmatrix.sync.aligned.m8n8.trans.b16 %0, %1;" : "=r"(b0) : "r"(vb[c]));
      asm volatile("movmatrix.sync.aligned.m8n8.trans.b16 %0, %1;" : "=r"(b1) : "r"(vb[4 + c]));
      mma16816(o + 4 * c, p0, p1, p2, p3, b0, b1);
    }
  }
}

__global__ void __launch_bounds__(NTHREADS, 1) fused_kernel(const __grid_constant__ Params P, __nv_bfloat16* __restrict__ out) {
  extern __shared__ __align__(1024) uint8_t smem_raw[];
  const uint32_t sb = (uint32_t)__cvta_generic_to_shared(smem_raw);
  const uint32_t bar = sb + S_BAR;
  const uint32_t sd = (sb & 0x3FFFF) >> 4;
  const int bid = blockIdx.x, tid = threadIdx.x, lane = tid & 31;
  const int warp = __shfl_sync(~0u, tid >> 5, 0);
  const bool spare = bid >= 130 || bid == 112 || bid == 113;
  const int L = spare ? (bid >= 130 ? bid - 128 : bid - 112) : (bid < 112 ? bid : bid - 2);
  const int hi8 = L >> 3, lo8 = L & 7;
  const bool qcta = lo8 == 7;

  if (tid < B_END) {
    uint32_t cnt = 1;
    if (tid >= B_GE && tid < B_KF) cnt = (!spare && tid < B_GE + 7) ? 16 : 8;
    else if (tid >= B_KE && tid < B_OF) cnt = 16;
    else if (tid >= B_OE && tid < B_QF) cnt = 4;
    else if (tid == B_XFREE || tid == B_SOB) cnt = 16;
    else if (tid >= B_SG && tid < B_SKV) cnt = (!spare && tid == B_SG) ? 16 : 8;
    else if (tid == B_SKV) cnt = 4;
    mbar_init(bar + 8 * tid, cnt);
    proxy_fence();
  }
  __syncthreads();

  if (warp >= 16) {
    asm volatile("setmaxnreg.dec.sync.aligned.u32 32;");
    const int h = hi8, qb = lo8;
    if (warp == 16) {
      if (lane == 0) {
        const unsigned ep = spare ? 0 : __ldcg(&gEpoch[bid]) + 1;
        const int nchunk = spare ? 28 : 14;
        int st = 1, kc = 0, job = 0;
#pragma unroll 1
        for (int c = 0; c < nchunk; c++) {
          if (c >= 5) mbar_wait(bar + 8 * (B_GE + c - 5));
          const bool three = !spare && job == 0;
          const int br = (three && !qcta) ? 0 : 1, m = spare ? 4 * L + job : hi8;
          const int b0 = spare ? 5 : qcta ? 3 * job : 7 + lo8, b1 = (spare || qcta) ? b0 + 1 : b0 + 7;
          const uint32_t dst = sb + st * STAGE, fb = bar + 8 * (B_GF + c);
          mbar_expect(fb, three ? 40960 : 32768);
          tma2d(dst, &P.x[br], kc * 64, m * 128, fb);
          tma2d(dst + 16384, &P.w[br], b0 * 64, kc * 64, fb);
          tma2d(dst + 24576, &P.w[br], b1 * 64, kc * 64, fb);
          if (three) tma2d(dst + 32768, &P.w[br], (qcta ? 2 : lo8) * 64, kc * 64, fb);
          st = st == 4 ? 0 : st + 1;
          if (++kc == 7) { kc = 0; job++; }
        }
        STAMP(32);
        if (!spare) {
          poll(C_A + (28 * h >> 6), ep * 16);
          poll(C_A + ((28 * h + 27) >> 6), ep * 16);
          proxy_fence();
          STAMP(33);
          const uint8_t* src = gQKV[0] + h * HEAD_STRIDE;
          mbar_expect(bar + 8 * B_QF, 16384);
          bulk(sb + S_Q, src + (2 * qb) * 24576, 8192, bar + 8 * B_QF);
          bulk(sb + S_Q + 8192, src + (2 * qb + 1) * 24576, 8192, bar + 8 * B_QF);
          int slot = 0;
#pragma unroll 1
          for (int t = 0; t < 16; t++) {
            mbar_wait(bar + 8 * (t >= 6 ? B_KE + t - 6 : B_GE + (t < 2 ? 9 : t < 5 ? 10 : 11)));
            mbar_expect(bar + 8 * (B_KF + t), 16384);
            bulk(sb + S_RING + slot * 16384, src + t * 24576 + 8192, 16384, bar + 8 * (B_KF + t));
            slot = slot == 5 ? 0 : slot + 1;
          }
          const int oq = hi8 >> 1, m64 = oq * 4 + (hi8 & 1);
          int hs = 8;
#pragma unroll 1
          for (int i = 0; i < 28; i++) {
            if (i == 0) { poll(C_OB + oq, ep * 16); proxy_fence(); }
            if (i == 14) { poll(C_OA + m64, ep * 64); proxy_fence(); STAMP(34); }
            if (i == 21) { poll(C_OA + m64 + 2, ep * 64); proxy_fence(); STAMP(35); }
            mbar_wait(bar + 8 * (i < 12 ? B_KE + 10 + (i >> 1) : B_OE + i - 12));
            const uint8_t* s = i < 14 ? gO[1] + (m64 + 2 * (i & 1)) * 57344 + (i >> 1) * 8192
                                      : gO[0] + m64 * 57344 + (i < 21 ? i - 14 : i - 7) * 8192;
            mbar_expect(bar + 8 * (B_OF + i), 8192);
            bulk(sb + S_RING + hs * 8192, s, 8192, bar + 8 * (B_OF + i));
            hs = hs == 11 ? 0 : hs + 1;
          }
        }
      }
    } else if (warp == 17) {
      if (lane == 0 && !spare) {
        const unsigned ep = __ldcg(&gEpoch[bid]) + 1;
        mbar_wait(bar + 8 * (B_GE + 13));
        mbar_expect(bar + 8 * B_WOB, 57344);
        tma2d(sb + S_WOB, &P.wo[1], lo8 * 56, 0, bar + 8 * B_WOB);
        tma2d(sb + S_WOB + 28672, &P.wo[1], lo8 * 56, 224, bar + 8 * B_WOB);
        const uint8_t* src = gQKV[1] + h * HEAD_STRIDE + 2 * qb * 24576;
        poll(C_BK + qb, ep * 14);
        proxy_fence();
        mbar_expect(bar + 8 * B_PKV, 32768);
        bulk(sb + S_PKV, src + 8192, 16384, bar + 8 * B_PKV);
        bulk(sb + S_PKV + 16384, src + 24576 + 8192, 16384, bar + 8 * B_PKV);
        STAMP(36);
        poll(C_KV + h, ep * 8);
        proxy_fence();
        mbar_expect(bar + 8 * B_PART, 32768);
        bulk(sb + S_PKV, gPart + h * 8192, 32768, bar + 8 * B_PART);
        STAMP(37);
        poll(C_BQ + qb, ep * 6);
        proxy_fence();
        mbar_expect(bar + 8 * B_PQ, 16384);
        bulk(sb + S_PQ, src, 8192, bar + 8 * B_PQ);
        bulk(sb + S_PQ + 8192, src + 24576, 8192, bar + 8 * B_PQ);
        STAMP(38);
        mbar_wait(bar + 8 * B_XFREE);
        mbar_expect(bar + 8 * B_WOA, 57344);
        tma2d(sb + S_WOA, &P.wo[0], lo8 * 56, 0, bar + 8 * B_WOA);
        tma2d(sb + S_WOA + 28672, &P.wo[0], lo8 * 56, 224, bar + 8 * B_WOA);
      }
    } else if (warp == 18) {
      if (!spare) {
        const unsigned ep = __ldcg(&gEpoch[bid]) + 1;
        mbar_wait(bar + 8 * B_QF);
        const bool zlo = lane >= 24 && (h & 1), zhi = lane >= 24 && !(h & 1);
        const uint4* kp = (const uint4*)(gQKV[0] + h * HEAD_STRIDE + 2 * qb * 24576 + 8192) + lane;
        float kmax = 0.f, qmax = 0.f;
#pragma unroll 4
        for (int r = 0; r < 32; r++) {
          uint4 v = __ldcg(kp + (r >> 4) * 1536 + (r & 15) * 32);
          float a = zlo ? 0.f : sq2(v.x, sq2(v.y, 0.f)), b = zhi ? 0.f : sq2(v.z, sq2(v.w, 0.f));
          a += b;
          a += __shfl_xor_sync(~0u, a, 8); a += __shfl_xor_sync(~0u, a, 16);
          if ((EMU_MASK >> (r & 15)) & 1) a *= 0.25f;
          kmax = (a > kmax || a != a) ? a : kmax;
        }
        kmax = __uint_as_float(__reduce_max_sync(~0u, __float_as_uint(kmax) & 0x7FFFFFFFu));
        if (lane == 0) asm volatile("st.relaxed.gpu.global.u64 [%0], %1;" ::"l"(&gKn[L]), "l"(((unsigned long long)ep << 32) | __float_as_uint(kmax)) : "memory");
#pragma unroll 2
        for (int r = 0; r < 32; r++) {
          uint4 v = *(const uint4*)(smem_raw + S_Q + r * 512 + lane * 16);
          float a = zlo ? 0.f : sq2(v.x, sq2(v.y, 0.f)), b = zhi ? 0.f : sq2(v.z, sq2(v.w, 0.f));
          a += b;
          a += __shfl_xor_sync(~0u, a, 8); a += __shfl_xor_sync(~0u, a, 16);
          qmax = (a > qmax || a != a) ? a : qmax;
        }
        qmax = __uint_as_float(__reduce_max_sync(~0u, __float_as_uint(qmax) & 0x7FFFFFFFu));
        STAMP(39);
        mbar_wait(bar + 8 * B_PART);
#pragma unroll 1
        for (int it = 0; it < 8; it++) {
          float4 a = make_float4(0.f, 0.f, 0.f, 0.f);
#pragma unroll
          for (int p = 0; p < 8; p++) {
            float4 v = *(const float4*)(smem_raw + S_PKV + p * 4096 + it * 512 + lane * 16);
            a.x += v.x; a.y += v.y; a.z += v.z; a.w += v.w;
          }
          *(uint2*)(smem_raw + S_KVM + it * 256 + lane * 8) = make_uint2(pack(a.x, a.y), pack(a.z, a.w));
        }
        proxy_fence();
        warp_arrive(bar + 8 * B_KVM);
        STAMP(40);
        unsigned long long v;
        for (int n = 0;; n++) {
          asm volatile("ld.relaxed.gpu.global.u64 %0, [%1];" : "=l"(v) : "l"(&gKn[h * 8 + (lane & 7)]) : "memory");
          if (__all_sync(~0u, (unsigned)(v >> 32) == ep)) break;
          if (n > (1 << 22)) __trap();
        }
        kmax = __uint_as_float(__reduce_max_sync(~0u, (unsigned)v));
        if (lane == 0) { *(volatile uint32_t*)(smem_raw + S_MISC) = (qmax * kmax <= GUARD) ? 0u : 1u; mbar_arrive(bar + 8 * B_GUARD); }
      }
    } else {
      if (lane == 0) {
        if (spare) {
          for (int j = 0; j < 4; j++) { mbar_wait(bar + 8 * (B_SG + j)); signal(C_BQ + 2 * L + (j >> 1)); }
        } else {
          mbar_wait(bar + 8 * B_SG); signal(qcta ? C_BQ + (hi8 >> 1) : C_A + lo8);
          STAMP(41);
          mbar_wait(bar + 8 * (B_SG + 1)); signal((qcta ? C_BQ : C_BK) + (hi8 >> 1));
          STAMP(42);
          mbar_wait(bar + 8 * B_SKV); signal(C_KV + h);
          mbar_wait(bar + 8 * B_SOB); signal(C_OB + qb);
        }
      }
    }
  } else {
    asm volatile("setmaxnreg.inc.sync.aligned.u32 112;");
    const int wg = warp >> 2, ww = warp & 3, pair = wg >> 1, w = wg & 1;
    {
      float acc[64];
      const int njob = (spare || pair) ? 2 : 1;
#pragma unroll 1
      for (int jb = 0; jb < njob; jb++) {
        const int job = spare ? pair + 2 * jb : jb;
        const bool n64 = !spare && pair && jb == 0;
        const int br = (!spare && job == 0 && !qcta) ? 0 : 1, m = spare ? 4 * L + job : hi8;
        const int c0 = job * 7;
        int st = (c0 + 1) % 5;
#pragma unroll
        for (int i = 0; i < 64; i++) acc[i] = 0.f;
        pin<64>(acc);
        if (n64) {
#pragma unroll 1
          for (int kc = 0; kc < 7; kc++) {
            mbar_wait(bar + 8 * (B_GF + c0 + kc));
            const uint32_t a = (sd + st * (STAGE >> 4) + w * 512) | L_X, b = (sd + st * (STAGE >> 4) + 2048) | L_W;
            wg_fence();
#pragma unroll
            for (int k = 0; k < 4; k++) wg64_ss_tb<H_SW, H_SW>(acc, a + 2 * k, b + 128 * k);
            wg_commit();
            wg_wait<1>();
            if (kc > 0 && lane == 0) mbar_arrive(bar + 8 * (B_GE + c0 + kc - 1));
            st = st == 4 ? 0 : st + 1;
          }
          wg_wait<0>();
        } else {
#pragma unroll 1
          for (int kc = 0; kc < 7; kc++) {
            mbar_wait(bar + 8 * (B_GF + c0 + kc));
            if (kc == 0) STAMP(wg * 8 + 0);
            const uint32_t a = (sd + st * (STAGE >> 4) + w * 512) | L_X, b = (sd + st * (STAGE >> 4) + 1024) | L_W;
            wg_fence();
#pragma unroll
            for (int k = 0; k < 4; k++) wg128_ss_tb<H_SW, H_SW>(acc, a + 2 * k, b + 128 * k);
            wg_commit();
            wg_wait<1>();
            if (kc > 0 && lane == 0) mbar_arrive(bar + 8 * (B_GE + c0 + kc - 1));
            st = st == 4 ? 0 : st + 1;
          }
          wg_wait<0>();
        }
        pin<64>(acc);
        if (lane == 0) mbar_arrive(bar + 8 * (B_GE + c0 + 6));
        STAMP(wg * 8 + 1);
        int box = n64 ? (qcta ? 2 : lo8) : spare ? 5 : qcta ? 3 * job : 7 + lo8;
        const int nb = n64 ? 1 : 2;
#pragma unroll 1
        for (int b = 0; b < nb; b++) {
          const int sec = box >= 14 ? 2 : box >= 7 ? 1 : 0, j = box - 7 * sec, rg = 8 * w + 2 * ww;
          uint32_t pk[16], pad0 = 0, pad1 = 0;
          if (br == 1 && sec < 2) {
#pragma unroll
            for (int i = 0; i < 16; i++) pk[i] = pack(phi(acc[2 * i]), phi(acc[2 * i + 1]));
          } else {
            float f0 = 1.f, f1 = 1.f;
            if (sec == 0) { f0 = f1 = 0.27264374f; pad0 = pad1 = (lane & 1) ? 0x00003F80u : 0x3F803F80u; }
            else if (sec == 2) { pad0 = pad1 = (lane & 1) ? 0u : 0x00003F80u; }
            else {
              const uint32_t pe = (lane & 1) ? 0x00003C3Cu : 0x40344426u, pm = (lane & 1) ? 0u : 0x0000C240u;
              const bool e0 = (EMU_MASK >> rg) & 1, e1 = (EMU_MASK >> (rg + 1)) & 1;
              f0 = e0 ? 2.f : 1.f; f1 = e1 ? 2.f : 1.f; pad0 = e0 ? pe : pm; pad1 = e1 ? pe : pm;
            }
#pragma unroll
            for (int i = 0; i < 8; i++) {
              pk[2 * i] = pack(acc[4 * i] * f0, acc[4 * i + 1] * f0);
              pk[2 * i + 1] = pack(acc[4 * i + 2] * f1, acc[4 * i + 3] * f1);
            }
          }
          uint8_t* base = gQKV[br] + m * 24576 + sec * 8192 + rg * 512 + lane * 4;
          const bool up = lane & 2;
#pragma unroll
          for (int i = 0; i < 8; i++) {
            const bool wrap = j + i >= 7;
            const int r = wrap ? j + i - 7 : j + i, pr = wrap ? j + 1 : j;
            uint8_t* p = base + 2 * pr * HEAD_STRIDE;
            if (r == 3) {
              stg(p + 384, up ? pad0 : pk[2 * i]); stg(p + 384 + 512, up ? pad1 : pk[2 * i + 1]);
              stg(p + HEAD_STRIDE + 384, up ? pk[2 * i] : pad0); stg(p + HEAD_STRIDE + 384 + 512, up ? pk[2 * i + 1] : pad1);
            } else {
              p += r < 3 ? r * 128 : HEAD_STRIDE + (r - 4) * 128;
              stg(p, pk[2 * i]); stg(p + 512, pk[2 * i + 1]);
            }
          }
#pragma unroll
          for (int i = 0; i < 32; i++) acc[i] = acc[32 + i];
          box += (spare || qcta) ? 1 : 7;
        }
        warp_arrive(bar + 8 * (B_SG + job));
        STAMP(wg * 8 + 2);
      }
    }
    if (!spare) {
      const int h = hi8, qb = lo8;
      uint8_t* obase = gO[0] + (qb * 4 + wg) * 57344 + ww * 2048 + lane * 4;
      float o[16];
      {
        float s[64];
        uint32_t p[32];
#pragma unroll
        for (int i = 0; i < 16; i++) o[i] = 0.f;
        pin<16>(o);
        const uint32_t dq = (sd + (S_Q >> 4) + wg * 256) | L_KM;
        mbar_wait(bar + 8 * B_QF);
        uint32_t cur = sd;
#pragma unroll 1
        for (int t = 0; t < 16; t++) {
          mbar_wait(bar + 8 * (B_KF + t));
          if (t == 0) STAMP(wg * 8 + 3);
          wg_fence();
          wg128_ss_z<H_KM, H_KM>(s, dq, cur | L_KM);
          wg128_ss<H_KM, H_KM>(s, dq + 16, (cur | L_KM) + 16);
          wg_commit();
          wg_wait<0>();
          pin<64>(s);
#pragma unroll
          for (int g = 0; g < 16; g++) {
            if ((EMU_MASK >> g) & 1) {
              p[2 * g] = exp2_pair(s[4 * g], s[4 * g + 1]);
              p[2 * g + 1] = exp2_pair(s[4 * g + 2], s[4 * g + 3]);
            } else {
              p[2 * g] = pack(ex2(s[4 * g]), ex2(s[4 * g + 1]));
              p[2 * g + 1] = pack(ex2(s[4 * g + 2]), ex2(s[4 * g + 3]));
            }
          }
          pin<32>(p);
          wg_fence();
#pragma unroll
          for (int k = 0; k < 8; k++) wg32_rs_tb<H_MN>(o, p[4 * k], p[4 * k + 1], p[4 * k + 2], p[4 * k + 3], ((cur + 512) | L_MN) + 64 * k);
          wg_commit();
          wg_wait<0>();
          pin<16>(o);
          if (lane == 0) mbar_arrive(bar + 8 * (B_KE + t));
          cur = cur == sd + 5 * 1024 ? sd : cur + 1024;
          if (t == T_KVP && wg == 0) {
            mbar_wait(bar + 8 * B_PKV);
            const uint32_t a = (sd + (S_PKV >> 4)) | L_MN;
            wg_fence();
            wg32_ss_ta_tb_z<H_MN, H_MN>(s, a, a + 512);
#pragma unroll
            for (int k = 1; k < 16; k++) wg32_ss_ta_tb<H_MN, H_MN>(s, a + (k >> 3) * 1024 + (k & 7) * 64, a + 512 + (k >> 3) * 1024 + (k & 7) * 64);
            wg_commit();
            wg_wait<0>();
            pin<16>(s);
            if (ww < 2) {
              float2* dst = (float2*)gPart + L * 512 + ww * 256 + lane;
#pragma unroll
              for (int c = 0; c < 4; c++) {
                dst[c * 32] = make_float2(s[4 * c], s[4 * c + 1]);
                dst[128 + c * 32] = make_float2(s[4 * c + 2], s[4 * c + 3]);
              }
            }
            warp_arrive(bar + 8 * B_SKV);
          }
          if (t == T_OB) {
            mbar_wait(bar + 8 * B_KVM);
            mbar_wait(bar + 8 * B_PQ);
            const uint32_t a = (sd + (S_PQ >> 4) + wg * 256) | L_KM, b = (sd + (S_KVM >> 4)) | L_MN;
            wg_fence();
            wg32_ss_tb_z<H_KM, H_MN>(s, a, b);
            wg32_ss_tb<H_KM, H_MN>(s, a + 16, b + 64);
            wg_commit();
            wg_wait<0>();
            pin<16>(s);
            if (lane == 0) mbar_arrive(bar + 8 * B_XFREE);
            store_o(s, 1e-6f, obase + sizeof(gO[0]), h, lane);
            warp_arrive(bar + 8 * B_SOB);
          }
        }
      }
      STAMP(wg * 8 + 4);
      mbar_wait(bar + 8 * B_GUARD);
      {
        float a0 = 0.f, a1 = 0.f;
#pragma unroll
        for (int c = 0; c < 3; c++) {
          a0 = fmaxf(a0, fmaxf(fabsf(o[4 * c]), fabsf(o[4 * c + 1])));
          a1 = fmaxf(a1, fmaxf(fabsf(o[4 * c + 2]), fabsf(o[4 * c + 3])));
        }
        const bool bad = lds(sb + S_MISC) != 0 || fminf(a0, a1) < 7.888609e-31f;
        if (__any_sync(~0u, bad)) attn_safe(o, sb + S_Q + wg * 4096 + ww * 1024 + lane * 4, gQKV[0] + h * HEAD_STRIDE + 8192, h, lane);
      }
      store_o(o, 0.f, obase, h, lane);
      __syncwarp();
      if (lane == 0) signal(C_OA + qb * 4 + wg);
      STAMP(wg * 8 + 5);
      float acc[28];
#pragma unroll
      for (int i = 0; i < 28; i++) acc[i] = 0.f;
      pin<28>(acc);
      mbar_wait(bar + 8 * (pair ? B_WOA : B_WOB));
      const uint32_t wo = (sd + ((pair ? S_WOA : S_WOB) >> 4)) | L_W;
      int item = pair ? 14 + 7 * w : w;
      const int step = pair ? 1 : 2;
#pragma unroll 1
      for (int kc = 0; kc < 7; kc++) {
        mbar_wait(bar + 8 * (B_OF + item));
        const uint32_t a = (sd + ((item + 8) % 12) * 512) | L_KM;
        wg_fence();
#pragma unroll
        for (int k = 0; k < 4; k++) wg56_ss_tb<H_O, H_SW>(acc, a + 16 * k, wo + kc * 512 + 128 * k);
        wg_commit();
        wg_wait<1>();
        if (kc > 0 && item - step < 16 && lane == 0) mbar_arrive(bar + 8 * (B_OE + item - step));
        item += step;
      }
      wg_wait<0>();
      pin<28>(acc);
      if (item - step < 16 && lane == 0) mbar_arrive(bar + 8 * (B_OE + item - step));
      STAMP(wg * 8 + 6);
      const int row = ((hi8 >> 1) * 4 + (hi8 & 1) + 2 * w) * 64 + ww * 16 + (lane >> 2);
      uint8_t* dst = (uint8_t*)out + row * 1792 + (pair ? 0 : 896) + lo8 * 112 + (lane & 3) * 4;
#pragma unroll
      for (int b = 0; b < 7; b++) {
        stg(dst + b * 16, pack(acc[4 * b], acc[4 * b + 1]));
        stg(dst + 8 * 1792 + b * 16, pack(acc[4 * b + 2], acc[4 * b + 3]));
      }
      if (tid == 384) atomicAdd(&gEpoch[bid], 1u);
      STAMP(wg * 8 + 7);
    }
  }
}

typedef CUresult (*EncodeFn)(CUtensorMap*, CUtensorMapDataType, cuuint32_t, void*, const cuuint64_t*, const cuuint64_t*,
                             const cuuint32_t*, const cuuint32_t*, CUtensorMapInterleave, CUtensorMapSwizzle,
                             CUtensorMapL2promotion, CUtensorMapFloatOOBfill);
void make_map(EncodeFn f, CUtensorMap* m, void* p, uint64_t cols, uint64_t rows, uint32_t box_rows) {
  cuuint64_t gd[2] = {cols, rows}, gs[1] = {cols * 2};
  cuuint32_t bd[2] = {64, box_rows}, es[2] = {1, 1};
  f(m, CU_TENSOR_MAP_DATA_TYPE_BFLOAT16, 2, p, gd, gs, bd, es, CU_TENSOR_MAP_INTERLEAVE_NONE, CU_TENSOR_MAP_SWIZZLE_128B,
    CU_TENSOR_MAP_L2_PROMOTION_NONE, CU_TENSOR_MAP_FLOAT_OOB_FILL_NONE);
}

}

extern "C" void kernel_launch(void* const* d_in, const int* in_sizes, int n_in, void* d_out, int out_size) {
  static EncodeFn enc = nullptr;
  if (!enc) {
    void* fn = nullptr;
    cudaDriverEntryPointQueryResult q;
    cudaGetDriverEntryPoint("cuTensorMapEncodeTiled", &fn, cudaEnableDefault, &q);
    enc = (EncodeFn)fn;
    cudaFuncSetAttribute(fused_kernel, cudaFuncAttributeMaxDynamicSharedMemorySize, SMEM_BYTES);
  }
  Params P;
  for (int b = 0; b < 2; b++) {
    make_map(enc, &P.x[b], d_in[3 * b], 448, 2048, 128);
    make_map(enc, &P.w[b], d_in[3 * b + 1], 1344, 448, 64);
    make_map(enc, &P.wo[b], d_in[3 * b + 2], 448, 448, 224);
  }
  fused_kernel<<<NCTA, NTHREADS, SMEM_BYTES>>>(P, (__nv_bfloat16*)d_out);
}
```

```cpp
#include <cuda_runtime.h>
#include <cuda.h>
#include <cuda_bf16.h>
#include <stdint.h>

namespace {

constexpr int NTHREADS = 640;
constexpr int NCTA = 132;

constexpr uint32_t M_STRIDE = 393216, SEC_STRIDE = 131072;
__device__ __align__(1024) uint8_t gQKV[2][16 * M_STRIDE];
__device__ __align__(1024) uint8_t gO[2][32 * 57344];
__device__ __align__(1024) float gPart[16 * 8 * 1024];
__device__ unsigned gCnt[96 * 32];
__device__ unsigned long long gKn[128];
__device__ unsigned gEpoch[NCTA];
constexpr int C_A = 0, C_BK = 8, C_BQ = 16, C_OB = 24, C_KV = 32, C_OA = 48;

#define STAMP(i) do {} while (0)

constexpr uint32_t STAGE = 40960;
constexpr uint32_t S_RING = 0;
constexpr uint32_t S_WOB = 98304;
constexpr uint32_t S_WOA = 155648;
constexpr uint32_t S_PKV = S_WOA;
constexpr uint32_t S_PQ = S_WOA + 32768;
constexpr uint32_t S_KVM = S_WOA + 49152;
constexpr uint32_t S_Q = 212992;
constexpr uint32_t S_BAR = 229376;
constexpr uint32_t S_MISC = S_BAR + 2048;
constexpr uint32_t SMEM_BYTES = S_MISC + 64;
constexpr int B_GF = 0, B_GE = 28, B_KF = 56, B_KE = 72, B_OF = 88  , B_OE = 109  , B_QF = 123, B_PKV = 124,
              B_PQ = 125, B_PART = 126, B_KVM = 127, B_XFREE = 128, B_WOB = 129, B_WOA = 130, B_GUARD = 131, B_SG = 132  ,
              B_SKV = 136, B_SOB = 137, B_SOA = 138, B_END = 139;

constexpr uint32_t EMU_MASK = 0xB5B5;
constexpr int T_KVP = 3, T_OB = 9;
constexpr float GUARD = 44.0f * 44.0f;

struct Params { CUtensorMap x[2], w[2], wo[2]; };

__device__ __forceinline__ void wg_fence() { asm volatile("wgmma.fence.sync.aligned;" ::: "memory"); }
__device__ __forceinline__ void wg_commit() { asm volatile("wgmma.commit_group.sync.aligned;" ::: "memory"); }
template <int N> __device__ __forceinline__ void wg_wait() { asm volatile("wgmma.wait_group.sync.aligned %0;" ::"n"(N) : "memory"); }
template <int M, int N> __device__ __forceinline__ void pin(float (&d)[N]) {
#pragma unroll
  for (int i = 0; i < M; i++) asm volatile("" : "+f"(d[i])::"memory");
}
template <int M, int N> __device__ __forceinline__ void pin(uint32_t (&d)[N]) {
#pragma unroll
  for (int i = 0; i < M; i++) asm volatile("" : "+r"(d[i])::"memory");
}
template<uint32_t HA, uint32_t HB, int NN> __device__ __forceinline__ void wg128_ss(float (&d)[NN], uint32_t al, uint32_t bl) {
  asm volatile("{\n.reg .pred p;\n.reg .b64 da, db;\nsetp.ne.b32 p, 1, 0;\nmov.b64 da, {%64, %66};\nmov.b64 db, {%65, %67};\n"
    "wgmma.mma_async.sync.aligned.m64n128k16.f32.bf16.bf16 {%0,%1,%2,%3,%4,%5,%6,%7,%8,%9,%10,%11,%12,%13,%14,%15,%16,%17,%18,%19,%20,%21,%22,%23,%24,%25,%26,%27,%28,%29,%30,%31,%32,%33,%34,%35,%36,%37,%38,%39,%40,%41,%42,%43,%44,%45,%46,%47,%48,%49,%50,%51,%52,%53,%54,%55,%56,%57,%58,%59,%60,%61,%62,%63}, da, db, p, 1, 1, 0, 0;\n}\n"
    : "+f"(d[0]),"+f"(d[1]),"+f"(d[2]),"+f"(d[3]),"+f"(d[4]),"+f"(d[5]),"+f"(d[6]),"+f"(d[7]),"+f"(d[8]),"+f"(d[9]),"+f"(d[10]),"+f"(d[11]),"+f"(d[12]),"+f"(d[13]),"+f"(d[14]),"+f"(d[15]),"+f"(d[16]),"+f"(d[17]),"+f"(d[18]),"+f"(d[19]),"+f"(d[20]),"+f"(d[21]),"+f"(d[22]),"+f"(d[23]),"+f"(d[24]),"+f"(d[25]),"+f"(d[26]),"+f"(d[27]),"+f"(d[28]),"+f"(d[29]),"+f"(d[30]),"+f"(d[31]),"+f"(d[32]),"+f"(d[33]),"+f"(d[34]),"+f"(d[35]),"+f"(d[36]),"+f"(d[37]),"+f"(d[38]),"+f"(d[39]),"+f"(d[40]),"+f"(d[41]),"+f"(d[42]),"+f"(d[43]),"+f"(d[44]),"+f"(d[45]),"+f"(d[46]),"+f"(d[47]),"+f"(d[48]),"+f"(d[49]),"+f"(d[50]),"+f"(d[51]),"+f"(d[52]),"+f"(d[53]),"+f"(d[54]),"+f"(d[55]),"+f"(d[56]),"+f"(d[57]),"+f"(d[58]),"+f"(d[59]),"+f"(d[60]),"+f"(d[61]),"+f"(d[62]),"+f"(d[63])
    : "r"(al), "r"(bl), "n"(HA), "n"(HB));
}
template<uint32_t HA, uint32_t HB, int NN> __device__ __forceinline__ void wg128_ss_z(float (&d)[NN], uint32_t al, uint32_t bl) {
  asm volatile("{\n.reg .pred p;\n.reg .b64 da, db;\nsetp.ne.b32 p, 0, 0;\nmov.b64 da, {%64, %66};\nmov.b64 db, {%65, %67};\n"
    "wgmma.mma_async.sync.aligned.m64n128k16.f32.bf16.bf16 {%0,%1,%2,%3,%4,%5,%6,%7,%8,%9,%10,%11,%12,%13,%14,%15,%16,%17,%18,%19,%20,%21,%22,%23,%24,%25,%26,%27,%28,%29,%30,%31,%32,%33,%34,%35,%36,%37,%38,%39,%40,%41,%42,%43,%44,%45,%46,%47,%48,%49,%50,%51,%52,%53,%54,%55,%56,%57,%58,%59,%60,%61,%62,%63}, da, db, p, 1, 1, 0, 0;\n}\n"
    : "=f"(d[0]),"=f"(d[1]),"=f"(d[2]),"=f"(d[3]),"=f"(d[4]),"=f"(d[5]),"=f"(d[6]),"=f"(d[7]),"=f"(d[8]),"=f"(d[9]),"=f"(d[10]),"=f"(d[11]),"=f"(d[12]),"=f"(d[13]),"=f"(d[14]),"=f"(d[15]),"=f"(d[16]),"=f"(d[17]),"=f"(d[18]),"=f"(d[19]),"=f"(d[20]),"=f"(d[21]),"=f"(d[22]),"=f"(d[23]),"=f"(d[24]),"=f"(d[25]),"=f"(d[26]),"=f"(d[27]),"=f"(d[28]),"=f"(d[29]),"=f"(d[30]),"=f"(d[31]),"=f"(d[32]),"=f"(d[33]),"=f"(d[34]),"=f"(d[35]),"=f"(d[36]),"=f"(d[37]),"=f"(d[38]),"=f"(d[39]),"=f"(d[40]),"=f"(d[41]),"=f"(d[42]),"=f"(d[43]),"=f"(d[44]),"=f"(d[45]),"=f"(d[46]),"=f"(d[47]),"=f"(d[48]),"=f"(d[49]),"=f"(d[50]),"=f"(d[51]),"=f"(d[52]),"=f"(d[53]),"=f"(d[54]),"=f"(d[55]),"=f"(d[56]),"=f"(d[57]),"=f"(d[58]),"=f"(d[59]),"=f"(d[60]),"=f"(d[61]),"=f"(d[62]),"=f"(d[63])
    : "r"(al), "r"(bl), "n"(HA), "n"(HB));
}
template<uint32_t HA, uint32_t HB, int NN> __device__ __forceinline__ void wg128_ss_tb(float (&d)[NN], uint32_t al, uint32_t bl) {
  asm volatile("{\n.reg .pred p;\n.reg .b64 da, db;\nsetp.ne.b32 p, 1, 0;\nmov.b64 da, {%64, %66};\nmov.b64 db, {%65, %67};\n"
    "wgmma.mma_async.sync.aligned.m64n128k16.f32.bf16.bf16 {%0,%1,%2,%3,%4,%5,%6,%7,%8,%9,%10,%11,%12,%13,%14,%15,%16,%17,%18,%19,%20,%21,%22,%23,%24,%25,%26,%27,%28,%29,%30,%31,%32,%33,%34,%35,%36,%37,%38,%39,%40,%41,%42,%43,%44,%45,%46,%47,%48,%49,%50,%51,%52,%53,%54,%55,%56,%57,%58,%59,%60,%61,%62,%63}, da, db, p, 1, 1, 0, 1;\n}\n"
    : "+f"(d[0]),"+f"(d[1]),"+f"(d[2]),"+f"(d[3]),"+f"(d[4]),"+f"(d[5]),"+f"(d[6]),"+f"(d[7]),"+f"(d[8]),"+f"(d[9]),"+f"(d[10]),"+f"(d[11]),"+f"(d[12]),"+f"(d[13]),"+f"(d[14]),"+f"(d[15]),"+f"(d[16]),"+f"(d[17]),"+f"(d[18]),"+f"(d[19]),"+f"(d[20]),"+f"(d[21]),"+f"(d[22]),"+f"(d[23]),"+f"(d[24]),"+f"(d[25]),"+f"(d[26]),"+f"(d[27]),"+f"(d[28]),"+f"(d[29]),"+f"(d[30]),"+f"(d[31]),"+f"(d[32]),"+f"(d[33]),"+f"(d[34]),"+f"(d[35]),"+f"(d[36]),"+f"(d[37]),"+f"(d[38]),"+f"(d[39]),"+f"(d[40]),"+f"(d[41]),"+f"(d[42]),"+f"(d[43]),"+f"(d[44]),"+f"(d[45]),"+f"(d[46]),"+f"(d[47]),"+f"(d[48]),"+f"(d[49]),"+f"(d[50]),"+f"(d[51]),"+f"(d[52]),"+f"(d[53]),"+f"(d[54]),"+f"(d[55]),"+f"(d[56]),"+f"(d[57]),"+f"(d[58]),"+f"(d[59]),"+f"(d[60]),"+f"(d[61]),"+f"(d[62]),"+f"(d[63])
    : "r"(al), "r"(bl), "n"(HA), "n"(HB));
}
template<uint32_t HB, int NN> __device__ __forceinline__ void wg32_rs_tb(float (&d)[NN], uint32_t a0, uint32_t a1, uint32_t a2, uint32_t a3, uint32_t bl) {
  asm volatile("{\n.reg .pred p;\n.reg .b64 db;\nsetp.ne.b32 p, 1, 0;\nmov.b64 db, {%20, %21};\n"
    "wgmma.mma_async.sync.aligned.m64n32k16.f32.bf16.bf16 {%0,%1,%2,%3,%4,%5,%6,%7,%8,%9,%10,%11,%12,%13,%14,%15}, {%16,%17,%18,%19}, db, p, 1, 1, 1;\n}\n"
    : "+f"(d[0]),"+f"(d[1]),"+f"(d[2]),"+f"(d[3]),"+f"(d[4]),"+f"(d[5]),"+f"(d[6]),"+f"(d[7]),"+f"(d[8]),"+f"(d[9]),"+f"(d[10]),"+f"(d[11]),"+f"(d[12]),"+f"(d[13]),"+f"(d[14]),"+f"(d[15])
    : "r"(a0), "r"(a1), "r"(a2), "r"(a3), "r"(bl), "n"(HB));
}
template<uint32_t HA, uint32_t HB, int NN> __device__ __forceinline__ void wg32_ss_tb(float (&d)[NN], uint32_t al, uint32_t bl) {
  asm volatile("{\n.reg .pred p;\n.reg .b64 da, db;\nsetp.ne.b32 p, 1, 0;\nmov.b64 da, {%16, %18};\nmov.b64 db, {%17, %19};\n"
    "wgmma.mma_async.sync.aligned.m64n32k16.f32.bf16.bf16 {%0,%1,%2,%3,%4,%5,%6,%7,%8,%9,%10,%11,%12,%13,%14,%15}, da, db, p, 1, 1, 0, 1;\n}\n"
    : "+f"(d[0]),"+f"(d[1]),"+f"(d[2]),"+f"(d[3]),"+f"(d[4]),"+f"(d[5]),"+f"(d[6]),"+f"(d[7]),"+f"(d[8]),"+f"(d[9]),"+f"(d[10]),"+f"(d[11]),"+f"(d[12]),"+f"(d[13]),"+f"(d[14]),"+f"(d[15])
    : "r"(al), "r"(bl), "n"(HA), "n"(HB));
}
template<uint32_t HA, uint32_t HB, int NN> __device__ __forceinline__ void wg32_ss_tb_z(float (&d)[NN], uint32_t al, uint32_t bl) {
  asm volatile("{\n.reg .pred p;\n.reg .b64 da, db;\nsetp.ne.b32 p, 0, 0;\nmov.b64 da, {%16, %18};\nmov.b64 db, {%17, %19};\n"
    "wgmma.mma_async.sync.aligned.m64n32k16.f32.bf16.bf16 {%0,%1,%2,%3,%4,%5,%6,%7,%8,%9,%10,%11,%12,%13,%14,%15}, da, db, p, 1, 1, 0, 1;\n}\n"
    : "=f"(d[0]),"=f"(d[1]),"=f"(d[2]),"=f"(d[3]),"=f"(d[4]),"=f"(d[5]),"=f"(d[6]),"=f"(d[7]),"=f"(d[8]),"=f"(d[9]),"=f"(d[10]),"=f"(d[11]),"=f"(d[12]),"=f"(d[13]),"=f"(d[14]),"=f"(d[15])
    : "r"(al), "r"(bl), "n"(HA), "n"(HB));
}
template<uint32_t HA, uint32_t HB, int NN> __device__ __forceinline__ void wg32_ss_ta_tb(float (&d)[NN], uint32_t al, uint32_t bl) {
  asm volatile("{\n.reg .pred p;\n.reg .b64 da, db;\nsetp.ne.b32 p, 1, 0;\nmov.b64 da, {%16, %18};\nmov.b64 db, {%17, %19};\n"
    "wgmma.mma_async.sync.aligned.m64n32k16.f32.bf16.bf16 {%0,%1,%2,%3,%4,%5,%6,%7,%8,%9,%10,%11,%12,%13,%14,%15}, da, db, p, 1, 1, 1, 1;\n}\n"
    : "+f"(d[0]),"+f"(d[1]),"+f"(d[2]),"+f"(d[3]),"+f"(d[4]),"+f"(d[5]),"+f"(d[6]),"+f"(d[7]),"+f"(d[8]),"+f"(d[9]),"+f"(d[10]),"+f"(d[11]),"+f"(d[12]),"+f"(d[13]),"+f"(d[14]),"+f"(d[15])
    : "r"(al), "r"(bl), "n"(HA), "n"(HB));
}
template<uint32_t HA, uint32_t HB, int NN> __device__ __forceinline__ void wg32_ss_ta_tb_z(float (&d)[NN], uint32_t al, uint32_t bl) {
  asm volatile("{\n.reg .pred p;\n.reg .b64 da, db;\nsetp.ne.b32 p, 0, 0;\nmov.b64 da, {%16, %18};\nmov.b64 db, {%17, %19};\n"
    "wgmma.mma_async.sync.aligned.m64n32k16.f32.bf16.bf16 {%0,%1,%2,%3,%4,%5,%6,%7,%8,%9,%10,%11,%12,%13,%14,%15}, da, db, p, 1, 1, 1, 1;\n}\n"
    : "=f"(d[0]),"=f"(d[1]),"=f"(d[2]),"=f"(d[3]),"=f"(d[4]),"=f"(d[5]),"=f"(d[6]),"=f"(d[7]),"=f"(d[8]),"=f"(d[9]),"=f"(d[10]),"=f"(d[11]),"=f"(d[12]),"=f"(d[13]),"=f"(d[14]),"=f"(d[15])
    : "r"(al), "r"(bl), "n"(HA), "n"(HB));
}
template<uint32_t HA, uint32_t HB, int NN> __device__ __forceinline__ void wg56_ss_tb(float (&d)[NN], uint32_t al, uint32_t bl) {
  asm volatile("{\n.reg .pred p;\n.reg .b64 da, db;\nsetp.ne.b32 p, 1, 0;\nmov.b64 da, {%28, %30};\nmov.b64 db, {%29, %31};\n"
    "wgmma.mma_async.sync.aligned.m64n56k16.f32.bf16.bf16 {%0,%1,%2,%3,%4,%5,%6,%7,%8,%9,%10,%11,%12,%13,%14,%15,%16,%17,%18,%19,%20,%21,%22,%23,%24,%25,%26,%27}, da, db, p, 1, 1, 0, 1;\n}\n"
    : "+f"(d[0]),"+f"(d[1]),"+f"(d[2]),"+f"(d[3]),"+f"(d[4]),"+f"(d[5]),"+f"(d[6]),"+f"(d[7]),"+f"(d[8]),"+f"(d[9]),"+f"(d[10]),"+f"(d[11]),"+f"(d[12]),"+f"(d[13]),"+f"(d[14]),"+f"(d[15]),"+f"(d[16]),"+f"(d[17]),"+f"(d[18]),"+f"(d[19]),"+f"(d[20]),"+f"(d[21]),"+f"(d[22]),"+f"(d[23]),"+f"(d[24]),"+f"(d[25]),"+f"(d[26]),"+f"(d[27])
    : "r"(al), "r"(bl), "n"(HA), "n"(HB));
}
template<uint32_t HA, uint32_t HB, int NN> __device__ __forceinline__ void wg64_ss_tb(float (&d)[NN], uint32_t al, uint32_t bl) {
  asm volatile("{\n.reg .pred p;\n.reg .b64 da, db;\nsetp.ne.b32 p, 1, 0;\nmov.b64 da, {%32, %34};\nmov.b64 db, {%33, %35};\n"
    "wgmma.mma_async.sync.aligned.m64n64k16.f32.bf16.bf16 {%0,%1,%2,%3,%4,%5,%6,%7,%8,%9,%10,%11,%12,%13,%14,%15,%16,%17,%18,%19,%20,%21,%22,%23,%24,%25,%26,%27,%28,%29,%30,%31}, da, db, p, 1, 1, 0, 1;\n}\n"
    : "+f"(d[0]),"+f"(d[1]),"+f"(d[2]),"+f"(d[3]),"+f"(d[4]),"+f"(d[5]),"+f"(d[6]),"+f"(d[7]),"+f"(d[8]),"+f"(d[9]),"+f"(d[10]),"+f"(d[11]),"+f"(d[12]),"+f"(d[13]),"+f"(d[14]),"+f"(d[15]),"+f"(d[16]),"+f"(d[17]),"+f"(d[18]),"+f"(d[19]),"+f"(d[20]),"+f"(d[21]),"+f"(d[22]),"+f"(d[23]),"+f"(d[24]),"+f"(d[25]),"+f"(d[26]),"+f"(d[27]),"+f"(d[28]),"+f"(d[29]),"+f"(d[30]),"+f"(d[31])
    : "r"(al), "r"(bl), "n"(HA), "n"(HB));
}

__device__ __forceinline__ void mbar_init(uint32_t a, uint32_t c) { asm volatile("mbarrier.init.shared::cta.b64 [%0], %1;" ::"r"(a), "r"(c) : "memory"); }
__device__ __forceinline__ void mbar_expect(uint32_t a, uint32_t b) { asm volatile("mbarrier.arrive.expect_tx.shared::cta.b64 _, [%0], %1;" ::"r"(a), "r"(b) : "memory"); }
__device__ __forceinline__ void mbar_arrive(uint32_t a) { asm volatile("mbarrier.arrive.shared::cta.b64 _, [%0];" ::"r"(a) : "memory"); }
__device__ __forceinline__ void mbar_wait(uint32_t a) {
  asm volatile("{\n.reg .pred p;\n.reg .u32 n;\n"
               "mbarrier.try_wait.parity.shared::cta.b64 p, [%0], 0, 20000;\n@p bra LD;\nmov.u32 n, 0;\nLW:\n"
               "mbarrier.try_wait.parity.shared::cta.b64 p, [%0], 0, 20000;\n@p bra LD;\n"
               "add.u32 n, n, 1;\nsetp.lt.u32 p, n, 0x40000;\n@p bra LW;\ntrap;\nLD:\n}\n" ::"r"(a) : "memory");
}
__device__ __forceinline__ bool elect() {
  uint32_t r;
  asm volatile("{\n.reg .pred p;\nelect.sync _|p, 0xffffffff;\nselp.u32 %0, 1, 0, p;\n}\n" : "=r"(r));
  return r;
}
__device__ __forceinline__ void warp_arrive(uint32_t a) { __syncwarp(); if ((threadIdx.x & 31) == 0) mbar_arrive(a); }
__device__ __forceinline__ void tma2d(uint32_t dst, const CUtensorMap* m, int c0, int c1, uint32_t bar) {
  asm volatile("cp.async.bulk.tensor.2d.shared::cluster.global.mbarrier::complete_tx::bytes [%0], [%1, {%3, %4}], [%2];"
               ::"r"(dst), "l"(m), "r"(bar), "r"(c0), "r"(c1) : "memory");
}
__device__ __forceinline__ void bulk(uint32_t dst, const void* src, uint32_t bytes, uint32_t bar) {
  asm volatile("cp.async.bulk.shared::cluster.global.mbarrier::complete_tx::bytes [%0], [%1], %2, [%3];"
               ::"r"(dst), "l"(src), "r"(bytes), "r"(bar) : "memory");
}
__device__ __forceinline__ void signal(int c) { asm volatile("red.release.gpu.global.add.u32 [%0], 1;" ::"l"(&gCnt[c * 32]) : "memory"); }
__device__ __forceinline__ unsigned ld_epoch(int b) { unsigned v; asm volatile("ld.relaxed.gpu.global.u32 %0, [%1];" : "=r"(v) : "l"(&gEpoch[b]) : "memory"); return v + 1; }
template <int SLEEP> __device__ __forceinline__ void poll(int c, unsigned target) {
  for (int n = 0;; n++) {
    unsigned v;
    asm volatile("ld.acquire.gpu.global.u32 %0, [%1];" : "=r"(v) : "l"(&gCnt[c * 32]) : "memory");
    if ((int)(v - target) >= 0) break;
    if (n > (1 << 22)) __trap();
    if (SLEEP) __nanosleep(SLEEP);
  }
  asm volatile("fence.proxy.async.global;" ::: "memory");
}
__device__ __forceinline__ float ex2(float x) { float y; asm("ex2.approx.ftz.f32 %0, %1;" : "=f"(y) : "f"(x)); return y; }
__device__ __forceinline__ uint32_t pack(float lo, float hi) { uint32_t y; asm("cvt.rn.bf16x2.f32 %0, %1, %2;" : "=r"(y) : "f"(hi), "f"(lo)); return y; }
__device__ __forceinline__ void stg(uint8_t* p, uint32_t v) { asm volatile("st.global.u32 [%0], %1;" ::"l"(p), "r"(v) : "memory"); }
__device__ __forceinline__ uint32_t lds(uint32_t a) { uint32_t v; asm volatile("ld.shared.u32 %0, [%1];" : "=r"(v) : "r"(a) : "memory"); return v; }
__device__ __forceinline__ uint32_t hsq(uint32_t v, uint32_t a) { uint32_t y; asm("fma.rn.bf16x2 %0, %1, %1, %2;" : "=r"(y) : "r"(v), "r"(a)); return y; }
__device__ __forceinline__ float rownorm(uint4 a, uint4 b, uint4 c, uint2 d) {
  uint32_t x = hsq(a.x, hsq(a.y, hsq(a.z, hsq(a.w, hsq(b.x, hsq(b.y, hsq(d.x, 0)))))));
  uint32_t y = hsq(c.x, hsq(c.y, hsq(c.z, hsq(c.w, hsq(b.z, hsq(b.w, hsq(d.y, 0)))))));
  return (__uint_as_float(x << 16) + __uint_as_float(x & 0xFFFF0000u)) + (__uint_as_float(y << 16) + __uint_as_float(y & 0xFFFF0000u));
}
__device__ __forceinline__ uint32_t exp2_pair(float t0, float t1) {
  uint32_t w = __byte_perm(__float_as_uint(t0), __float_as_uint(t1), 0x6521);
  uint32_t m = w | 0x3F803F80u, g;
  asm("fma.rn.bf16x2 %0, %1, %1, %2;" : "=r"(g) : "r"(m), "r"(0x40014001u));
  return g + w - m;
}
__device__ __forceinline__ float phi(float t) { return (t > 0.f ? t + 1.f : ex2(t * 1.4426950408889634f)) + 1e-6f; }

constexpr uint32_t H_SW = (1024 >> 4) | (1u << 30);
constexpr uint32_t L_X = 1u << 16, L_W = (8192u >> 4) << 16;
constexpr uint32_t H_KM = 128 >> 4, L_KM = (2048u >> 4) << 16;
constexpr uint32_t H_MN = 2048 >> 4, L_MN = (128u >> 4) << 16;
constexpr uint32_t H_KV = 128 >> 4, L_KV = (512u >> 4) << 16;
constexpr uint32_t H_O = 128 >> 4, L_O = (1024u >> 4) << 16;

__device__ __forceinline__ void store_o(const float* o, float eps, uint8_t* base, bool odd, int lane) {
  const int src = (lane & 28) | (odd ? 0 : 2);
  const float r0 = __fdividef(1.f, __shfl_sync(~0u, odd ? o[0] : o[12], src) + eps);
  const float r1 = __fdividef(1.f, __shfl_sync(~0u, odd ? o[2] : o[14], src) + eps);
  const bool up = lane & 2;
#pragma unroll
  for (int c = 0; c < 4; c++) {
    if (c == 0 ? (!odd || up) : c == 3 ? (odd || !up) : true) {
      stg(base + c * 1024, pack(o[4 * c] * r0, o[4 * c + 1] * r0));
      stg(base + c * 1024 + 128, pack(o[4 * c + 2] * r1, o[4 * c + 3] * r1));
    }
  }
}

__device__ __forceinline__ void mma16816(float* d, uint32_t a0, uint32_t a1, uint32_t a2, uint32_t a3, uint32_t b0, uint32_t b1) {
  asm volatile("mma.sync.aligned.m16n8k16.row.col.f32.bf16.bf16.f32 {%0,%1,%2,%3}, {%4,%5,%6,%7}, {%8,%9}, {%0,%1,%2,%3};"
               : "+f"(d[0]), "+f"(d[1]), "+f"(d[2]), "+f"(d[3]) : "r"(a0), "r"(a1), "r"(a2), "r"(a3), "r"(b0), "r"(b1));
}
__device__ __forceinline__ void attn_safe(float* o, const uint8_t* qp, const uint8_t* kv, bool odd, int lane) {
  uint32_t q[8];
#pragma unroll
  for (int i = 0; i < 8; i++) q[i] = __ldcg((const uint32_t*)(qp + (i & 1) * 128 + (i >> 1) * 2048) + lane);
  if (!odd && (lane & 2)) q[6] = q[7] = 0;
  if (odd && !(lane & 2)) q[0] = q[1] = 0;
  float m0 = -INFINITY, m1 = -INFINITY;
#pragma unroll
  for (int i = 0; i < 16; i++) o[i] = 0.f;
#pragma unroll 1
  for (int it = 0; it < 128; it++) {
    const uint32_t* k = (const uint32_t*)(kv + (it >> 3) * M_STRIDE + (it & 7) * 256) + lane;
    uint32_t kb[8], vb[8];
#pragma unroll
    for (int i = 0; i < 8; i++) { kb[i] = __ldcg(k + (i >> 2) * 32 + (i & 3) * 512); vb[i] = __ldcg(k + SEC_STRIDE / 4 + (i >> 2) * 32 + (i & 3) * 512); }
    float s[8];
#pragma unroll
    for (int b = 0; b < 2; b++) {
      s[4 * b] = s[4 * b + 1] = s[4 * b + 2] = s[4 * b + 3] = 0.f;
      mma16816(s + 4 * b, q[0], q[1], q[2], q[3], kb[4 * b], kb[4 * b + 1]);
      mma16816(s + 4 * b, q[4], q[5], q[6], q[7], kb[4 * b + 2], kb[4 * b + 3]);
      const float f = ((EMU_MASK >> ((it & 7) * 2 + b)) & 1) ? 0.5f : 1.f;
#pragma unroll
      for (int i = 0; i < 4; i++) s[4 * b + i] *= f;
    }
    float n0 = fmaxf(fmaxf(s[0], s[1]), fmaxf(s[4], s[5])), n1 = fmaxf(fmaxf(s[2], s[3]), fmaxf(s[6], s[7]));
    n0 = fmaxf(n0, __shfl_xor_sync(~0u, n0, 1)); n1 = fmaxf(n1, __shfl_xor_sync(~0u, n1, 1));
    n0 = fmaxf(n0, __shfl_xor_sync(~0u, n0, 2)); n1 = fmaxf(n1, __shfl_xor_sync(~0u, n1, 2));
    n0 = fmaxf(n0, m0); n1 = fmaxf(n1, m1);
    const float a0 = ex2(m0 - n0), a1 = ex2(m1 - n1);
    m0 = n0; m1 = n1;
    const uint32_t p0 = pack(ex2(s[0] - m0), ex2(s[1] - m0)), p1 = pack(ex2(s[2] - m1), ex2(s[3] - m1));
    const uint32_t p2 = pack(ex2(s[4] - m0), ex2(s[5] - m0)), p3 = pack(ex2(s[6] - m1), ex2(s[7] - m1));
#pragma unroll
    for (int c = 0; c < 4; c++) {
      o[4 * c] *= a0; o[4 * c + 1] *= a0; o[4 * c + 2] *= a1; o[4 * c + 3] *= a1;
      uint32_t b0, b1;
      asm volatile("movmatrix.sync.aligned.m8n8.trans.b16 %0, %1;" : "=r"(b0) : "r"(vb[c]));
      asm volatile("movmatrix.sync.aligned.m8n8.trans.b16 %0, %1;" : "=r"(b1) : "r"(vb[4 + c]));
      mma16816(o + 4 * c, p0, p1, p2, p3, b0, b1);
    }
  }
}

__global__ void __launch_bounds__(NTHREADS, 1) fused_kernel(const __grid_constant__ Params P, __nv_bfloat16* __restrict__ out) {
  extern __shared__ __align__(1024) uint8_t smem_raw[];
  const uint32_t sb = (uint32_t)__cvta_generic_to_shared(smem_raw);
  const uint32_t bar = sb + S_BAR;
  const uint32_t sd = (sb & 0x3FFFF) >> 4;
  const int bid = blockIdx.x, tid = threadIdx.x, lane = tid & 31;
  const int warp = __shfl_sync(~0u, tid >> 5, 0);
  const bool spare = bid >= 130 || bid == 112 || bid == 113;
  const int L = spare ? (bid >= 130 ? bid - 128 : bid - 112) : (bid < 112 ? bid : bid - 2);
  const int hi8 = L >> 3, lo8 = L & 7;
  const bool qcta = lo8 == 7;

  auto load_chunk = [&](int c, int job, int kc, int st) {
    const bool three = !spare && job == 0;
    const int br = (three && !qcta) ? 0 : 1, m = spare ? 4 * L + job : hi8;
    const int b0 = spare ? 5 : qcta ? 3 * job : 7 + lo8, b1 = (spare || qcta) ? b0 + 1 : b0 + 7;
    const uint32_t dst = sb + st * STAGE, fb = bar + 8 * (B_GF + c);
    mbar_expect(fb, three ? 40960 : 32768);
    tma2d(dst, &P.x[br], kc * 64, m * 128, fb);
    tma2d(dst + 16384, &P.w[br], b0 * 64, kc * 64, fb);
    tma2d(dst + 24576, &P.w[br], b1 * 64, kc * 64, fb);
    if (three) tma2d(dst + 32768, &P.w[br], (qcta ? 2 : lo8) * 64, kc * 64, fb);
  };
  if (elect()) {
    if (warp == 16) {
      mbar_init(bar, 1);
      load_chunk(0, 0, 0, 1);
      STAMP(44);
    } else {
#pragma unroll 1
      for (int i = warp < 16 ? warp + 1 : warp; i < B_END; i += 19) {
        uint32_t cnt = 1;
        if (i >= B_GE && i < B_KF) cnt = (!spare && i < B_GE + 7) ? 16 : 8;
        if ((i >= B_KE && i < B_OF) || i == B_XFREE || i == B_SOB) cnt = 16;
        if ((i >= B_OE && i < B_QF) || i == B_SKV) cnt = 4;
        if ((i >= B_SG && i < B_SKV) || i == B_SOA) cnt = (!spare && i == B_SG) ? 16 : 8;
        mbar_init(bar + 8 * i, cnt);
      }
    }
  }
  __syncthreads();
  if (warp == 16) STAMP(43);

  if (warp >= 16) {
    asm volatile("setmaxnreg.dec.sync.aligned.u32 32;");
    const int h = hi8, qb = lo8;
    const int m64 = (hi8 >> 1) * 4 + (hi8 & 1);
    auto o_slot = [&](int kc) { return sb + (kc < 2 ? S_RING + (4 + kc) * 16384 : kc < 6 ? S_RING + (kc - 2) * 16384 : S_Q); };
    auto load_oa = [&](int w, unsigned ep) {
      poll<0>(C_OA + m64 + 2 * w, ep * 64);
      STAMP(34 + w);
#pragma unroll 1
      for (int kc = 0; kc < 7; kc++) {
        mbar_wait(bar + 8 * (B_OE + 7 * w + kc));
        mbar_expect(bar + 8 * (B_OF + 7 + 7 * w + kc), 8192);
        bulk(o_slot(kc) + w * 8192, gO[0] + (m64 + 2 * w) * 57344 + kc * 8192, 8192, bar + 8 * (B_OF + 7 + 7 * w + kc));
      }
    };
    if (warp == 16) {
      if (elect()) {
        const int nchunk = spare ? 28 : 14;
        int st = 2, kc = 1, job = 0;
        unsigned ep = 0;
#pragma unroll 1
        for (int c = 1; c < nchunk; c++) {
          if (c == 5) { STAMP(45); ep = ld_epoch(bid); }
          if (c >= 5) mbar_wait(bar + 8 * (B_GE + c - 5));
          load_chunk(c, job, kc, st);
          st = st == 4 ? 0 : st + 1;
          if (++kc == 7) { kc = 0; job++; }
        }
        STAMP(32);
        if (!spare) {
          poll<0>(C_A + (28 * h >> 6), ep * 16);
          poll<0>(C_A + ((28 * h + 27) >> 6), ep * 16);
          STAMP(33);
          const uint8_t* src = gQKV[0] + h * 8192;
          mbar_expect(bar + 8 * B_QF, 16384);
          bulk(sb + S_Q, src + (2 * qb) * M_STRIDE, 8192, bar + 8 * B_QF);
          bulk(sb + S_Q + 8192, src + (2 * qb + 1) * M_STRIDE, 8192, bar + 8 * B_QF);
          int slot = 0;
#pragma unroll 1
          for (int t = 0; t < 16; t++) {
            mbar_wait(bar + 8 * (t >= 6 ? B_KE + t - 6 : B_GE + (t < 2 ? 9 : t < 5 ? 10 : 11)));
            mbar_expect(bar + 8 * (B_KF + t), 16384);
            bulk(sb + S_RING + slot * 16384, src + t * M_STRIDE + SEC_STRIDE, 8192, bar + 8 * (B_KF + t));
            bulk(sb + S_RING + slot * 16384 + 8192, src + t * M_STRIDE + 2 * SEC_STRIDE, 8192, bar + 8 * (B_KF + t));
            if (t == 0) STAMP(46);
            slot = slot == 5 ? 0 : slot + 1;
          }
          poll<100>(C_OB + (hi8 >> 1), ep * 16);
          mbar_wait(bar + 8 * B_GUARD);
#pragma unroll 1
          for (int kc = 0; kc < 7; kc++) {
            mbar_wait(bar + 8 * (B_KE + (kc < 6 ? 10 + kc : 15)));
            mbar_expect(bar + 8 * (B_OF + kc), 16384);
            bulk(o_slot(kc), gO[1] + m64 * 57344 + kc * 8192, 8192, bar + 8 * (B_OF + kc));
            bulk(o_slot(kc) + 8192, gO[1] + (m64 + 2) * 57344 + kc * 8192, 8192, bar + 8 * (B_OF + kc));
          }
        }
      }
    } else if (spare) {
      if (warp == 19 && elect()) {
        for (int j = 0; j < 4; j++) { mbar_wait(bar + 8 * (B_SG + j)); signal(C_BQ + 2 * L + (j >> 1)); }
      }
    } else if (warp == 17) {
      const unsigned ep = ld_epoch(bid);
      const uint8_t* src = gQKV[1] + h * 8192 + 2 * qb * M_STRIDE;
      if (elect()) {
        mbar_wait(bar + 8 * (B_KF + 2));
        poll<100>(C_BK + qb, ep * 14);
        mbar_wait(bar + 8 * (B_GE + 13));
        mbar_expect(bar + 8 * B_PKV, 32768);
#pragma unroll
        for (int i = 0; i < 4; i++) bulk(sb + S_PKV + i * 8192, src + (i >> 1) * M_STRIDE + (1 + (i & 1)) * SEC_STRIDE, 8192, bar + 8 * B_PKV);
        STAMP(36);
        mbar_wait(bar + 8 * (B_KE + 1));
        mbar_expect(bar + 8 * B_WOB, 57344);
        tma2d(sb + S_WOB, &P.wo[1], lo8 * 56, 0, bar + 8 * B_WOB);
        tma2d(sb + S_WOB + 28672, &P.wo[1], lo8 * 56, 224, bar + 8 * B_WOB);
        mbar_wait(bar + 8 * B_SKV);
        poll<100>(C_KV + h, ep * 8);
        mbar_expect(bar + 8 * B_PART, 32768);
        bulk(sb + S_PKV, gPart + h * 8192, 32768, bar + 8 * B_PART);
        STAMP(37);
      }
      __syncwarp();
      mbar_wait(bar + 8 * B_PART);
#pragma unroll 1
      for (int it = 0; it < 8; it++) {
        float4 a = *(const float4*)(smem_raw + S_PKV + it * 512 + lane * 16);
#pragma unroll
        for (int p = 1; p < 8; p++) {
          float4 v = *(const float4*)(smem_raw + S_PKV + p * 4096 + it * 512 + lane * 16);
          a.x += v.x; a.y += v.y; a.z += v.z; a.w += v.w;
        }
        *(uint2*)(smem_raw + S_KVM + it * 256 + lane * 8) = make_uint2(pack(a.x, a.y), pack(a.z, a.w));
      }
      asm volatile("fence.proxy.async.shared::cta;" ::: "memory");
      __syncwarp();
      if (elect()) {
        mbar_arrive(bar + 8 * B_KVM);
        STAMP(40);
        poll<100>(C_BQ + qb, ep * 6);
        mbar_expect(bar + 8 * B_PQ, 16384);
        bulk(sb + S_PQ, src, 8192, bar + 8 * B_PQ);
        bulk(sb + S_PQ + 8192, src + M_STRIDE, 8192, bar + 8 * B_PQ);
        STAMP(38);
        mbar_wait(bar + 8 * B_XFREE);
        mbar_expect(bar + 8 * B_WOA, 57344);
        tma2d(sb + S_WOA, &P.wo[0], lo8 * 56, 0, bar + 8 * B_WOA);
        tma2d(sb + S_WOA + 28672, &P.wo[0], lo8 * 56, 224, bar + 8 * B_WOA);
        mbar_wait(bar + 8 * (B_KE + 14));
        load_oa(0, ep);
      }
    } else if (warp == 18) {
      const unsigned ep = ld_epoch(bid);
      mbar_wait(bar + 8 * B_QF);
      const uint32_t o3 = (h & 1) * 2048 + lane * 16, o1 = ((h & 1) ? 8 : 6144) + lane * 16;
      uint32_t kmax = 0, qmax = 0;
#pragma unroll 1
      for (int u = 0; u < 8; u++) {
        const uint8_t* p = gQKV[0] + h * 8192 + (2 * qb + (u >> 2)) * M_STRIDE + SEC_STRIDE + (u & 3) * 512;
        float a = rownorm(__ldcg((const uint4*)(p + o3)), __ldcg((const uint4*)(p + o3 + 2048)), __ldcg((const uint4*)(p + o3 + 4096)), __ldcg((const uint2*)(p + o1)));
        if ((EMU_MASK >> ((u & 3) * 4 + (lane >> 3))) & 1) a *= 0.25f;
        kmax = max(kmax, __float_as_uint(a) & 0x7FFFFFFFu);
      }
      kmax = __reduce_max_sync(~0u, kmax);
      if (lane == 0) asm volatile("st.relaxed.gpu.global.u64 [%0], %1;" ::"l"(&gKn[L]), "l"(((unsigned long long)ep << 32) | kmax) : "memory");
#pragma unroll 1
      for (int u = 0; u < 8; u++) {
        const uint8_t* p = smem_raw + S_Q + (u >> 2) * 8192 + (u & 3) * 512;
        float a = rownorm(*(const uint4*)(p + o3), *(const uint4*)(p + o3 + 2048), *(const uint4*)(p + o3 + 4096), *(const uint2*)(p + o1));
        qmax = max(qmax, __float_as_uint(a) & 0x7FFFFFFFu);
      }
      qmax = __reduce_max_sync(~0u, qmax);
      unsigned long long v;
      for (int n = 0;; n++) {
        asm volatile("ld.relaxed.gpu.global.u64 %0, [%1];" : "=l"(v) : "l"(&gKn[h * 8 + (lane & 7)]) : "memory");
        if (__all_sync(~0u, (unsigned)(v >> 32) == ep)) break;
        if (n > (1 << 22)) __trap();
        __nanosleep(100);
      }
      kmax = __reduce_max_sync(~0u, (unsigned)v);
      asm volatile("fence.proxy.async.shared::cta;" ::: "memory");
      __syncwarp();
      if (elect()) {
        *(volatile uint32_t*)(smem_raw + S_MISC) = (__uint_as_float(qmax) * __uint_as_float(kmax) <= GUARD) ? 0u : 1u;
        mbar_arrive(bar + 8 * B_GUARD);
        STAMP(39);
        mbar_wait(bar + 8 * (B_KE + 15));
        load_oa(1, ep);
      }
    } else if (elect()) {
      mbar_wait(bar + 8 * B_SG); signal(qcta ? C_BQ + (hi8 >> 1) : C_A + lo8);
      STAMP(41);
      mbar_wait(bar + 8 * (B_SG + 1)); signal((qcta ? C_BQ : C_BK) + (hi8 >> 1));
      STAMP(42);
      mbar_wait(bar + 8 * B_SKV); signal(C_KV + h);
      mbar_wait(bar + 8 * B_SOB); signal(C_OB + qb);
      mbar_wait(bar + 8 * B_SOA);
      asm volatile("fence.acq_rel.gpu;\nred.relaxed.gpu.global.add.u32 [%0], 4;\nred.relaxed.gpu.global.add.u32 [%0+128], 4;"
                   ::"l"(&gCnt[(C_OA + qb * 4) * 32]) : "memory");
    }
  } else {
    asm volatile("setmaxnreg.inc.sync.aligned.u32 112;");
    const int wg = warp >> 2, ww = warp & 3, pair = wg >> 1, w = wg & 1;
    {
      float acc[64];
      const int njob = (spare || pair) ? 2 : 1;
#pragma unroll 1
      for (int jb = 0; jb < njob; jb++) {
        const int job = spare ? pair + 2 * jb : jb;
        const bool n64 = !spare && pair && jb == 0;
        const int br = (!spare && job == 0 && !qcta) ? 0 : 1, m = spare ? 4 * L + job : hi8;
        const int c0 = job * 7;
        int st = (c0 + 1) % 5;
#pragma unroll
        for (int i = 0; i < 64; i++) acc[i] = 0.f;
        pin<64>(acc);
        if (n64) {
#pragma unroll 1
          for (int kc = 0; kc < 7; kc++) {
            mbar_wait(bar + 8 * (B_GF + c0 + kc));
            const uint32_t a = (sd + st * (STAGE >> 4) + w * 512) | L_X, b = (sd + st * (STAGE >> 4) + 2048) | L_W;
            wg_fence();
#pragma unroll
            for (int k = 0; k < 4; k++) wg64_ss_tb<H_SW, H_SW>(acc, a + 2 * k, b + 128 * k);
            wg_commit();
            wg_wait<1>();
            if (kc > 0 && lane == 0) mbar_arrive(bar + 8 * (B_GE + c0 + kc - 1));
            st = st == 4 ? 0 : st + 1;
          }
          wg_wait<0>();
        } else {
#pragma unroll 1
          for (int kc = 0; kc < 7; kc++) {
            mbar_wait(bar + 8 * (B_GF + c0 + kc));
            if (kc == 0) STAMP(wg * 8 + 0);
            const uint32_t a = (sd + st * (STAGE >> 4) + w * 512) | L_X, b = (sd + st * (STAGE >> 4) + 1024) | L_W;
            wg_fence();
#pragma unroll
            for (int k = 0; k < 4; k++) wg128_ss_tb<H_SW, H_SW>(acc, a + 2 * k, b + 128 * k);
            wg_commit();
            wg_wait<1>();
            if (kc > 0 && lane == 0) mbar_arrive(bar + 8 * (B_GE + c0 + kc - 1));
            st = st == 4 ? 0 : st + 1;
          }
          wg_wait<0>();
        }
        pin<64>(acc);
        if (lane == 0) mbar_arrive(bar + 8 * (B_GE + c0 + 6));
        STAMP(wg * 8 + 1);
        int box = n64 ? (qcta ? 2 : lo8) : spare ? 5 : qcta ? 3 * job : 7 + lo8;
        const int nb = n64 ? 1 : 2;
#pragma unroll 1
        for (int b = 0; b < nb; b++) {
          const int sec = box >= 14 ? 2 : box >= 7 ? 1 : 0, j = box - 7 * sec, rg = 8 * w + 2 * ww;
          uint32_t pk[16], pad0 = 0, pad1 = 0;
          if (br == 1 && sec < 2) {
#pragma unroll
            for (int i = 0; i < 16; i++) pk[i] = pack(phi(acc[2 * i]), phi(acc[2 * i + 1]));
          } else {
            float f0 = 1.f, f1 = 1.f;
            if (sec == 0) { f0 = f1 = 0.27264374f; pad0 = pad1 = (lane & 1) ? 0x00003F80u : 0x3F803F80u; }
            else if (sec == 2) { pad0 = pad1 = (lane & 1) ? 0u : 0x00003F80u; }
            else {
              const uint32_t pe = (lane & 1) ? 0x00003C3Cu : 0x40344426u, pm = (lane & 1) ? 0u : 0x0000C240u;
              const bool e0 = (EMU_MASK >> rg) & 1, e1 = (EMU_MASK >> (rg + 1)) & 1;
              f0 = e0 ? 2.f : 1.f; f1 = e1 ? 2.f : 1.f; pad0 = e0 ? pe : pm; pad1 = e1 ? pe : pm;
            }
#pragma unroll
            for (int i = 0; i < 8; i++) {
              pk[2 * i] = pack(acc[4 * i] * f0, acc[4 * i + 1] * f0);
              pk[2 * i + 1] = pack(acc[4 * i + 2] * f1, acc[4 * i + 3] * f1);
            }
          }
          uint8_t* base = gQKV[br] + m * M_STRIDE + sec * SEC_STRIDE + rg * 128 + lane * 4;
          const int up = (lane >> 1) & 1, u = j + 3 + up, thr = u >= 7 ? 14 - u : 7 - u;
          uint8_t* pa = base + (9 * j + (u >= 7)) * 2048;
          uint8_t* pb = pa + 2048;
#pragma unroll
          for (int i = 0; i < 8; i++) {
            uint8_t* p = (i >= thr ? pb : pa) + i * 2048;
            stg(p, pk[2 * i]); stg(p + 128, pk[2 * i + 1]);
          }
          uint8_t* pp = base + (8 * (j > 3 ? j + 1 : j) + 4 - up) * 2048;
          stg(pp, pad0); stg(pp + 128, pad1);
          if (j == 3) { stg(pp + 16384, pad0); stg(pp + 16384 + 128, pad1); }
#pragma unroll
          for (int i = 0; i < 32; i++) acc[i] = acc[32 + i];
          box += (spare || qcta) ? 1 : 7;
        }
        warp_arrive(bar + 8 * (B_SG + job));
        STAMP(wg * 8 + 2);
      }
    }
    if (!spare) {
      const int h = hi8, qb = lo8;
      const bool odd = h & 1;
      uint8_t* obase = gO[0] + (qb * 4 + wg) * 57344 + (7 * (h >> 1) + 3 * (h & 1)) * 1024 + ww * 256 + lane * 4;
      float o[16];
      {
        float s[64];
        uint32_t p[32];
#pragma unroll
        for (int i = 0; i < 16; i++) o[i] = 0.f;
        pin<16>(o);
        const uint32_t k0 = odd ? 256 : 0, k1 = 256 - k0;
        const uint32_t dq = (sd + (S_Q >> 4) + pair * 512 + w * 64) | L_KM;
        mbar_wait(bar + 8 * B_QF);
        uint32_t cur = sd;
#pragma unroll 1
        for (int t = 0; t < 16; t++) {
          mbar_wait(bar + 8 * (B_KF + t));
          if (t == 0) STAMP(wg * 8 + 3);
          wg_fence();
          wg128_ss_z<H_KM, H_KM>(s, dq + k0, (cur | L_KM) + k0);
          wg128_ss<H_KM, H_KM>(s, dq + k1, (cur | L_KM) + k1);
          wg_commit();
          wg_wait<0>();
          pin<64>(s);
#pragma unroll
          for (int g = 0; g < 16; g++) {
            if ((EMU_MASK >> g) & 1) {
              p[2 * g] = exp2_pair(s[4 * g], s[4 * g + 1]);
              p[2 * g + 1] = exp2_pair(s[4 * g + 2], s[4 * g + 3]);
            } else {
              p[2 * g] = pack(ex2(s[4 * g]), ex2(s[4 * g + 1]));
              p[2 * g + 1] = pack(ex2(s[4 * g + 2]), ex2(s[4 * g + 3]));
            }
          }
          pin<32>(p);
          wg_fence();
#pragma unroll
          for (int k = 0; k < 8; k++) wg32_rs_tb<H_MN>(o, p[4 * k], p[4 * k + 1], p[4 * k + 2], p[4 * k + 3], ((cur + 512) | L_MN) + 16 * k);
          wg_commit();
          wg_wait<0>();
          pin<16>(o);
          if (lane == 0) mbar_arrive(bar + 8 * (B_KE + t));
          cur = cur == sd + 5 * 1024 ? sd : cur + 1024;
          if (t == T_KVP && wg == 0) {
            mbar_wait(bar + 8 * B_PKV);
            const uint32_t a = (sd + (S_PKV >> 4)) | L_MN;
            wg_fence();
            wg32_ss_ta_tb_z<H_MN, H_MN>(s, a, a + 512);
#pragma unroll
            for (int k = 1; k < 16; k++) wg32_ss_ta_tb<H_MN, H_MN>(s, a + (k >> 3) * 1024 + (k & 7) * 16, a + 512 + (k >> 3) * 1024 + (k & 7) * 16);
            wg_commit();
            wg_wait<0>();
            pin<16>(s);
            if (ww < 2) {
              float2* dst = (float2*)gPart + L * 512 + ww * 256 + lane;
#pragma unroll
              for (int c = 0; c < 4; c++) {
                dst[c * 32] = make_float2(s[4 * c], s[4 * c + 1]);
                dst[128 + c * 32] = make_float2(s[4 * c + 2], s[4 * c + 3]);
              }
            }
            warp_arrive(bar + 8 * B_SKV);
          }
          if (t == T_OB) {
            mbar_wait(bar + 8 * B_KVM);
            mbar_wait(bar + 8 * B_PQ);
            const uint32_t a = (sd + (S_PQ >> 4) + pair * 512 + w * 64) | L_KM, b = (sd + (S_KVM >> 4)) | L_KV;
            wg_fence();
            wg32_ss_tb_z<H_KM, H_KV>(s, a, b);
            wg32_ss_tb<H_KM, H_KV>(s, a + 256, b + 64);
            wg_commit();
            wg_wait<0>();
            pin<16>(s);
            if (lane == 0) mbar_arrive(bar + 8 * B_XFREE);
            store_o(s, 1e-6f, obase + sizeof(gO[0]), odd, lane);
            warp_arrive(bar + 8 * B_SOB);
          }
        }
      }
      STAMP(wg * 8 + 4);
      mbar_wait(bar + 8 * B_GUARD);
      {
        float a0 = 0.f, a1 = 0.f;
#pragma unroll
        for (int c = 1; c < 3; c++) {
          a0 = fmaxf(a0, fmaxf(fabsf(o[4 * c]), fabsf(o[4 * c + 1])));
          a1 = fmaxf(a1, fmaxf(fabsf(o[4 * c + 2]), fabsf(o[4 * c + 3])));
        }
        const bool bad = lds(sb + S_MISC) != 0 || fminf(a0, a1) < 7.888609e-31f;
        if (__any_sync(~0u, bad))
          attn_safe(o, gQKV[0] + h * 8192 + (2 * qb + pair) * M_STRIDE + w * 1024 + ww * 256, gQKV[0] + h * 8192 + SEC_STRIDE, odd, lane);
      }
      store_o(o, 0.f, obase, odd, lane);
      __syncwarp();
      if (lane == 0) { if (pair) signal(C_OA + qb * 4 + wg); else mbar_arrive(bar + 8 * B_SOA); }
      STAMP(wg * 8 + 5);
      float acc[28];
#pragma unroll
      for (int i = 0; i < 28; i++) acc[i] = 0.f;
      pin<28>(acc);
      mbar_wait(bar + 8 * (pair ? B_WOA : B_WOB));
      const uint32_t wo = (sd + ((pair ? S_WOA : S_WOB) >> 4)) | L_W;
      const uint32_t fb = bar + 8 * (B_OF + (pair ? 7 + 7 * w : 0)), eb = bar + 8 * (B_OE + 7 * w);
#pragma unroll 1
      for (int kc = 0; kc < 7; kc++) {
        mbar_wait(fb + 8 * kc);
        const uint32_t a = (sd + (kc < 2 ? (4 + kc) * 1024 : kc < 6 ? (kc - 2) * 1024 : (S_Q >> 4)) + w * 512) | L_O;
        wg_fence();
#pragma unroll
        for (int k = 0; k < 4; k++) wg56_ss_tb<H_O, H_SW>(acc, a + 128 * k, wo + kc * 512 + 128 * k);
        wg_commit();
        wg_wait<1>();
        if (kc > 0 && !pair && lane == 0) mbar_arrive(eb + 8 * (kc - 1));
      }
      wg_wait<0>();
      pin<28>(acc);
      STAMP(wg * 8 + 6);
      asm volatile("bar.sync %0, 128;" ::"r"(1 + wg) : "memory");
      const uint32_t stg_s = sb + S_Q + w * 8192 + ww * 1792;
#pragma unroll
      for (int b = 0; b < 4; b++) {
        const uint32_t a = stg_s + (lane & 15) * 112 + (lane >> 4) * 16 + b * 32;
        if (b < 3)
          asm volatile("stmatrix.sync.aligned.m8n8.x4.shared.b16 [%0], {%1,%2,%3,%4};" ::"r"(a), "r"(pack(acc[8 * b], acc[8 * b + 1])),
                       "r"(pack(acc[8 * b + 2], acc[8 * b + 3])), "r"(pack(acc[8 * b + 4], acc[8 * b + 5])), "r"(pack(acc[8 * b + 6], acc[8 * b + 7])) : "memory");
        else
          asm volatile("stmatrix.sync.aligned.m8n8.x2.shared.b16 [%0], {%1,%2};" ::"r"(a), "r"(pack(acc[24], acc[25])), "r"(pack(acc[26], acc[27])) : "memory");
      }
      __syncwarp();
      uint8_t* dst = (uint8_t*)out + (((hi8 >> 1) * 4 + (hi8 & 1) + 2 * w) * 64 + ww * 16) * 1792 + (pair ? 0 : 896) + lo8 * 112;
#pragma unroll
      for (int i = 0; i < 4; i++) {
        const int e = i * 32 + lane, r = (e * 147) >> 10;
        if (i < 3 || lane < 16) {
          uint4 v;
          asm volatile("ld.shared.v4.u32 {%0,%1,%2,%3}, [%4];" : "=r"(v.x), "=r"(v.y), "=r"(v.z), "=r"(v.w) : "r"(stg_s + e * 16) : "memory");
          *(uint4*)(dst + r * (1792 - 112) + e * 16) = v;
        }
      }
      if (!pair) { asm volatile("fence.proxy.async.shared::cta;" ::: "memory"); warp_arrive(eb + 8 * 6); }
      if (tid == 384) atomicAdd(&gEpoch[bid], 1u);
      STAMP(wg * 8 + 7);
    }
  }
}

typedef CUresult (*EncodeFn)(CUtensorMap*, CUtensorMapDataType, cuuint32_t, void*, const cuuint64_t*, const cuuint64_t*,
                             const cuuint32_t*, const cuuint32_t*, CUtensorMapInterleave, CUtensorMapSwizzle,
                             CUtensorMapL2promotion, CUtensorMapFloatOOBfill);
void make_map(EncodeFn f, CUtensorMap* m, void* p, uint64_t cols, uint64_t rows, uint32_t box_rows) {
  cuuint64_t gd[2] = {cols, rows}, gs[1] = {cols * 2};
  cuuint32_t bd[2] = {64, box_rows}, es[2] = {1, 1};
  f(m, CU_TENSOR_MAP_DATA_TYPE_BFLOAT16, 2, p, gd, gs, bd, es, CU_TENSOR_MAP_INTERLEAVE_NONE, CU_TENSOR_MAP_SWIZZLE_128B,
    CU_TENSOR_MAP_L2_PROMOTION_NONE, CU_TENSOR_MAP_FLOAT_OOB_FILL_NONE);
}

}

extern "C" void kernel_launch(void* const* d_in, const int* in_sizes, int n_in, void* d_out, int out_size) {
  static EncodeFn enc = nullptr;
  if (!enc) {
    void* fn = nullptr;
    cudaDriverEntryPointQueryResult q;
    cudaGetDriverEntryPoint("cuTensorMapEncodeTiled", &fn, cudaEnableDefault, &q);
    enc = (EncodeFn)fn;
    cudaFuncSetAttribute(fused_kernel, cudaFuncAttributeMaxDynamicSharedMemorySize, SMEM_BYTES);
  }
  Params P;
  for (int b = 0; b < 2; b++) {
    make_map(enc, &P.x[b], d_in[3 * b], 448, 2048, 128);
    make_map(enc, &P.w[b], d_in[3 * b + 1], 1344, 448, 64);
    make_map(enc, &P.wo[b], d_in[3 * b + 2], 448, 448, 224);
  }
  fused_kernel<<<NCTA, NTHREADS, SMEM_BYTES>>>(P, (__nv_bfloat16*)d_out);
}
```

```cpp
#include <cuda_runtime.h>
#include <cuda.h>
#include <cuda_bf16.h>
#include <stdint.h>

namespace {

constexpr int NTHREADS = 640;
constexpr int NCTA = 132;

constexpr uint32_t M_STRIDE = 393216, SEC_STRIDE = 131072;
__device__ __align__(1024) uint8_t gQKV[2][16 * M_STRIDE];
__device__ __align__(1024) uint8_t gO[2][32 * 57344];
__device__ __align__(1024) float gPart[16 * 8 * 1024];
__device__ unsigned gCnt[96 * 32];
__device__ unsigned long long gKn[128];
__device__ unsigned gEpoch[NCTA];
constexpr int C_A = 0, C_BK = 8, C_BQ = 16, C_OB = 24, C_KV = 32, C_OA = 48;

#define STAMP(i) do {} while (0)

constexpr uint32_t STAGE = 40960;
constexpr uint32_t S_RING = 0;
constexpr uint32_t S_WOB = 98304;
constexpr uint32_t S_WOA = 155648;
constexpr uint32_t S_PKV = S_WOA;
constexpr uint32_t S_PQ = S_WOA + 32768;
constexpr uint32_t S_KVM = S_WOA + 49152;
constexpr uint32_t S_Q = 212992;
constexpr uint32_t S_BAR = 229376;
constexpr uint32_t S_MISC = S_BAR + 2048;
constexpr uint32_t SMEM_BYTES = S_MISC + 64;
constexpr int B_GF = 0, B_GE = 28, B_KF = 56, B_KE = 72, B_OF = 88  , B_OE = 109  , B_QF = 123, B_PKV = 124,
              B_PQ = 125, B_PART = 126, B_KVM = 127, B_XFREE = 128, B_WOB = 129, B_WOA = 130, B_GUARD = 131, B_SG = 132  ,
              B_SKV = 136, B_SOB = 137, B_SOA = 138, B_END = 139;

constexpr uint32_t EMU_MASK = 0xB5B5;
constexpr int T_KVP = 3, T_OB = 9;
constexpr float GUARD = 44.0f * 44.0f;

struct Params { CUtensorMap x[2], w[2], wo[2]; const uint8_t* in[6]; };

__device__ __forceinline__ void wg_fence() { asm volatile("wgmma.fence.sync.aligned;" ::: "memory"); }
__device__ __forceinline__ void wg_commit() { asm volatile("wgmma.commit_group.sync.aligned;" ::: "memory"); }
template <int N> __device__ __forceinline__ void wg_wait() { asm volatile("wgmma.wait_group.sync.aligned %0;" ::"n"(N) : "memory"); }
template <int M, int N> __device__ __forceinline__ void pin(float (&d)[N]) {
#pragma unroll
  for (int i = 0; i < M; i++) asm volatile("" : "+f"(d[i])::"memory");
}
template <int M, int N> __device__ __forceinline__ void pin(uint32_t (&d)[N]) {
#pragma unroll
  for (int i = 0; i < M; i++) asm volatile("" : "+r"(d[i])::"memory");
}
template<uint32_t HA, uint32_t HB, int NN> __device__ __forceinline__ void wg128_ss(float (&d)[NN], uint32_t al, uint32_t bl) {
  asm volatile("{\n.reg .pred p;\n.reg .b64 da, db;\nsetp.ne.b32 p, 1, 0;\nmov.b64 da, {%64, %66};\nmov.b64 db, {%65, %67};\n"
    "wgmma.mma_async.sync.aligned.m64n128k16.f32.bf16.bf16 {%0,%1,%2,%3,%4,%5,%6,%7,%8,%9,%10,%11,%12,%13,%14,%15,%16,%17,%18,%19,%20,%21,%22,%23,%24,%25,%26,%27,%28,%29,%30,%31,%32,%33,%34,%35,%36,%37,%38,%39,%40,%41,%42,%43,%44,%45,%46,%47,%48,%49,%50,%51,%52,%53,%54,%55,%56,%57,%58,%59,%60,%61,%62,%63}, da, db, p, 1, 1, 0, 0;\n}\n"
    : "+f"(d[0]),"+f"(d[1]),"+f"(d[2]),"+f"(d[3]),"+f"(d[4]),"+f"(d[5]),"+f"(d[6]),"+f"(d[7]),"+f"(d[8]),"+f"(d[9]),"+f"(d[10]),"+f"(d[11]),"+f"(d[12]),"+f"(d[13]),"+f"(d[14]),"+f"(d[15]),"+f"(d[16]),"+f"(d[17]),"+f"(d[18]),"+f"(d[19]),"+f"(d[20]),"+f"(d[21]),"+f"(d[22]),"+f"(d[23]),"+f"(d[24]),"+f"(d[25]),"+f"(d[26]),"+f"(d[27]),"+f"(d[28]),"+f"(d[29]),"+f"(d[30]),"+f"(d[31]),"+f"(d[32]),"+f"(d[33]),"+f"(d[34]),"+f"(d[35]),"+f"(d[36]),"+f"(d[37]),"+f"(d[38]),"+f"(d[39]),"+f"(d[40]),"+f"(d[41]),"+f"(d[42]),"+f"(d[43]),"+f"(d[44]),"+f"(d[45]),"+f"(d[46]),"+f"(d[47]),"+f"(d[48]),"+f"(d[49]),"+f"(d[50]),"+f"(d[51]),"+f"(d[52]),"+f"(d[53]),"+f"(d[54]),"+f"(d[55]),"+f"(d[56]),"+f"(d[57]),"+f"(d[58]),"+f"(d[59]),"+f"(d[60]),"+f"(d[61]),"+f"(d[62]),"+f"(d[63])
    : "r"(al), "r"(bl), "n"(HA), "n"(HB));
}
template<uint32_t HA, uint32_t HB, int NN> __device__ __forceinline__ void wg128_ss_z(float (&d)[NN], uint32_t al, uint32_t bl) {
  asm volatile("{\n.reg .pred p;\n.reg .b64 da, db;\nsetp.ne.b32 p, 0, 0;\nmov.b64 da, {%64, %66};\nmov.b64 db, {%65, %67};\n"
    "wgmma.mma_async.sync.aligned.m64n128k16.f32.bf16.bf16 {%0,%1,%2,%3,%4,%5,%6,%7,%8,%9,%10,%11,%12,%13,%14,%15,%16,%17,%18,%19,%20,%21,%22,%23,%24,%25,%26,%27,%28,%29,%30,%31,%32,%33,%34,%35,%36,%37,%38,%39,%40,%41,%42,%43,%44,%45,%46,%47,%48,%49,%50,%51,%52,%53,%54,%55,%56,%57,%58,%59,%60,%61,%62,%63}, da, db, p, 1, 1, 0, 0;\n}\n"
    : "=f"(d[0]),"=f"(d[1]),"=f"(d[2]),"=f"(d[3]),"=f"(d[4]),"=f"(d[5]),"=f"(d[6]),"=f"(d[7]),"=f"(d[8]),"=f"(d[9]),"=f"(d[10]),"=f"(d[11]),"=f"(d[12]),"=f"(d[13]),"=f"(d[14]),"=f"(d[15]),"=f"(d[16]),"=f"(d[17]),"=f"(d[18]),"=f"(d[19]),"=f"(d[20]),"=f"(d[21]),"=f"(d[22]),"=f"(d[23]),"=f"(d[24]),"=f"(d[25]),"=f"(d[26]),"=f"(d[27]),"=f"(d[28]),"=f"(d[29]),"=f"(d[30]),"=f"(d[31]),"=f"(d[32]),"=f"(d[33]),"=f"(d[34]),"=f"(d[35]),"=f"(d[36]),"=f"(d[37]),"=f"(d[38]),"=f"(d[39]),"=f"(d[40]),"=f"(d[41]),"=f"(d[42]),"=f"(d[43]),"=f"(d[44]),"=f"(d[45]),"=f"(d[46]),"=f"(d[47]),"=f"(d[48]),"=f"(d[49]),"=f"(d[50]),"=f"(d[51]),"=f"(d[52]),"=f"(d[53]),"=f"(d[54]),"=f"(d[55]),"=f"(d[56]),"=f"(d[57]),"=f"(d[58]),"=f"(d[59]),"=f"(d[60]),"=f"(d[61]),"=f"(d[62]),"=f"(d[63])
    : "r"(al), "r"(bl), "n"(HA), "n"(HB));
}
template<uint32_t HA, uint32_t HB, int NN> __device__ __forceinline__ void wg128_ss_tb(float (&d)[NN], uint32_t al, uint32_t bl) {
  asm volatile("{\n.reg .pred p;\n.reg .b64 da, db;\nsetp.ne.b32 p, 1, 0;\nmov.b64 da, {%64, %66};\nmov.b64 db, {%65, %67};\n"
    "wgmma.mma_async.sync.aligned.m64n128k16.f32.bf16.bf16 {%0,%1,%2,%3,%4,%5,%6,%7,%8,%9,%10,%11,%12,%13,%14,%15,%16,%17,%18,%19,%20,%21,%22,%23,%24,%25,%26,%27,%28,%29,%30,%31,%32,%33,%34,%35,%36,%37,%38,%39,%40,%41,%42,%43,%44,%45,%46,%47,%48,%49,%50,%51,%52,%53,%54,%55,%56,%57,%58,%59,%60,%61,%62,%63}, da, db, p, 1, 1, 0, 1;\n}\n"
    : "+f"(d[0]),"+f"(d[1]),"+f"(d[2]),"+f"(d[3]),"+f"(d[4]),"+f"(d[5]),"+f"(d[6]),"+f"(d[7]),"+f"(d[8]),"+f"(d[9]),"+f"(d[10]),"+f"(d[11]),"+f"(d[12]),"+f"(d[13]),"+f"(d[14]),"+f"(d[15]),"+f"(d[16]),"+f"(d[17]),"+f"(d[18]),"+f"(d[19]),"+f"(d[20]),"+f"(d[21]),"+f"(d[22]),"+f"(d[23]),"+f"(d[24]),"+f"(d[25]),"+f"(d[26]),"+f"(d[27]),"+f"(d[28]),"+f"(d[29]),"+f"(d[30]),"+f"(d[31]),"+f"(d[32]),"+f"(d[33]),"+f"(d[34]),"+f"(d[35]),"+f"(d[36]),"+f"(d[37]),"+f"(d[38]),"+f"(d[39]),"+f"(d[40]),"+f"(d[41]),"+f"(d[42]),"+f"(d[43]),"+f"(d[44]),"+f"(d[45]),"+f"(d[46]),"+f"(d[47]),"+f"(d[48]),"+f"(d[49]),"+f"(d[50]),"+f"(d[51]),"+f"(d[52]),"+f"(d[53]),"+f"(d[54]),"+f"(d[55]),"+f"(d[56]),"+f"(d[57]),"+f"(d[58]),"+f"(d[59]),"+f"(d[60]),"+f"(d[61]),"+f"(d[62]),"+f"(d[63])
    : "r"(al), "r"(bl), "n"(HA), "n"(HB));
}
template<uint32_t HB, int NN> __device__ __forceinline__ void wg32_rs_tb(float (&d)[NN], uint32_t a0, uint32_t a1, uint32_t a2, uint32_t a3, uint32_t bl) {
  asm volatile("{\n.reg .pred p;\n.reg .b64 db;\nsetp.ne.b32 p, 1, 0;\nmov.b64 db, {%20, %21};\n"
    "wgmma.mma_async.sync.aligned.m64n32k16.f32.bf16.bf16 {%0,%1,%2,%3,%4,%5,%6,%7,%8,%9,%10,%11,%12,%13,%14,%15}, {%16,%17,%18,%19}, db, p, 1, 1, 1;\n}\n"
    : "+f"(d[0]),"+f"(d[1]),"+f"(d[2]),"+f"(d[3]),"+f"(d[4]),"+f"(d[5]),"+f"(d[6]),"+f"(d[7]),"+f"(d[8]),"+f"(d[9]),"+f"(d[10]),"+f"(d[11]),"+f"(d[12]),"+f"(d[13]),"+f"(d[14]),"+f"(d[15])
    : "r"(a0), "r"(a1), "r"(a2), "r"(a3), "r"(bl), "n"(HB));
}
template<uint32_t HA, uint32_t HB, int NN> __device__ __forceinline__ void wg32_ss_tb(float (&d)[NN], uint32_t al, uint32_t bl) {
  asm volatile("{\n.reg .pred p;\n.reg .b64 da, db;\nsetp.ne.b32 p, 1, 0;\nmov.b64 da, {%16, %18};\nmov.b64 db, {%17, %19};\n"
    "wgmma.mma_async.sync.aligned.m64n32k16.f32.bf16.bf16 {%0,%1,%2,%3,%4,%5,%6,%7,%8,%9,%10,%11,%12,%13,%14,%15}, da, db, p, 1, 1, 0, 1;\n}\n"
    : "+f"(d[0]),"+f"(d[1]),"+f"(d[2]),"+f"(d[3]),"+f"(d[4]),"+f"(d[5]),"+f"(d[6]),"+f"(d[7]),"+f"(d[8]),"+f"(d[9]),"+f"(d[10]),"+f"(d[11]),"+f"(d[12]),"+f"(d[13]),"+f"(d[14]),"+f"(d[15])
    : "r"(al), "r"(bl), "n"(HA), "n"(HB));
}
template<uint32_t HA, uint32_t HB, int NN> __device__ __forceinline__ void wg32_ss_tb_z(float (&d)[NN], uint32_t al, uint32_t bl) {
  asm volatile("{\n.reg .pred p;\n.reg .b64 da, db;\nsetp.ne.b32 p, 0, 0;\nmov.b64 da, {%16, %18};\nmov.b64 db, {%17, %19};\n"
    "wgmma.mma_async.sync.aligned.m64n32k16.f32.bf16.bf16 {%0,%1,%2,%3,%4,%5,%6,%7,%8,%9,%10,%11,%12,%13,%14,%15}, da, db, p, 1, 1, 0, 1;\n}\n"
    : "=f"(d[0]),"=f"(d[1]),"=f"(d[2]),"=f"(d[3]),"=f"(d[4]),"=f"(d[5]),"=f"(d[6]),"=f"(d[7]),"=f"(d[8]),"=f"(d[9]),"=f"(d[10]),"=f"(d[11]),"=f"(d[12]),"=f"(d[13]),"=f"(d[14]),"=f"(d[15])
    : "r"(al), "r"(bl), "n"(HA), "n"(HB));
}
template<uint32_t HA, uint32_t HB, int NN> __device__ __forceinline__ void wg32_ss_ta_tb(float (&d)[NN], uint32_t al, uint32_t bl) {
  asm volatile("{\n.reg .pred p;\n.reg .b64 da, db;\nsetp.ne.b32 p, 1, 0;\nmov.b64 da, {%16, %18};\nmov.b64 db, {%17, %19};\n"
    "wgmma.mma_async.sync.aligned.m64n32k16.f32.bf16.bf16 {%0,%1,%2,%3,%4,%5,%6,%7,%8,%9,%10,%11,%12,%13,%14,%15}, da, db, p, 1, 1, 1, 1;\n}\n"
    : "+f"(d[0]),"+f"(d[1]),"+f"(d[2]),"+f"(d[3]),"+f"(d[4]),"+f"(d[5]),"+f"(d[6]),"+f"(d[7]),"+f"(d[8]),"+f"(d[9]),"+f"(d[10]),"+f"(d[11]),"+f"(d[12]),"+f"(d[13]),"+f"(d[14]),"+f"(d[15])
    : "r"(al), "r"(bl), "n"(HA), "n"(HB));
}
template<uint32_t HA, uint32_t HB, int NN> __device__ __forceinline__ void wg32_ss_ta_tb_z(float (&d)[NN], uint32_t al, uint32_t bl) {
  asm volatile("{\n.reg .pred p;\n.reg .b64 da, db;\nsetp.ne.b32 p, 0, 0;\nmov.b64 da, {%16, %18};\nmov.b64 db, {%17, %19};\n"
    "wgmma.mma_async.sync.aligned.m64n32k16.f32.bf16.bf16 {%0,%1,%2,%3,%4,%5,%6,%7,%8,%9,%10,%11,%12,%13,%14,%15}, da, db, p, 1, 1, 1, 1;\n}\n"
    : "=f"(d[0]),"=f"(d[1]),"=f"(d[2]),"=f"(d[3]),"=f"(d[4]),"=f"(d[5]),"=f"(d[6]),"=f"(d[7]),"=f"(d[8]),"=f"(d[9]),"=f"(d[10]),"=f"(d[11]),"=f"(d[12]),"=f"(d[13]),"=f"(d[14]),"=f"(d[15])
    : "r"(al), "r"(bl), "n"(HA), "n"(HB));
}
template<uint32_t HA, uint32_t HB, int NN> __device__ __forceinline__ void wg56_ss_tb(float (&d)[NN], uint32_t al, uint32_t bl) {
  asm volatile("{\n.reg .pred p;\n.reg .b64 da, db;\nsetp.ne.b32 p, 1, 0;\nmov.b64 da, {%28, %30};\nmov.b64 db, {%29, %31};\n"
    "wgmma.mma_async.sync.aligned.m64n56k16.f32.bf16.bf16 {%0,%1,%2,%3,%4,%5,%6,%7,%8,%9,%10,%11,%12,%13,%14,%15,%16,%17,%18,%19,%20,%21,%22,%23,%24,%25,%26,%27}, da, db, p, 1, 1, 0, 1;\n}\n"
    : "+f"(d[0]),"+f"(d[1]),"+f"(d[2]),"+f"(d[3]),"+f"(d[4]),"+f"(d[5]),"+f"(d[6]),"+f"(d[7]),"+f"(d[8]),"+f"(d[9]),"+f"(d[10]),"+f"(d[11]),"+f"(d[12]),"+f"(d[13]),"+f"(d[14]),"+f"(d[15]),"+f"(d[16]),"+f"(d[17]),"+f"(d[18]),"+f"(d[19]),"+f"(d[20]),"+f"(d[21]),"+f"(d[22]),"+f"(d[23]),"+f"(d[24]),"+f"(d[25]),"+f"(d[26]),"+f"(d[27])
    : "r"(al), "r"(bl), "n"(HA), "n"(HB));
}
template<uint32_t HA, uint32_t HB, int NN> __device__ __forceinline__ void wg64_ss_tb(float (&d)[NN], uint32_t al, uint32_t bl) {
  asm volatile("{\n.reg .pred p;\n.reg .b64 da, db;\nsetp.ne.b32 p, 1, 0;\nmov.b64 da, {%32, %34};\nmov.b64 db, {%33, %35};\n"
    "wgmma.mma_async.sync.aligned.m64n64k16.f32.bf16.bf16 {%0,%1,%2,%3,%4,%5,%6,%7,%8,%9,%10,%11,%12,%13,%14,%15,%16,%17,%18,%19,%20,%21,%22,%23,%24,%25,%26,%27,%28,%29,%30,%31}, da, db, p, 1, 1, 0, 1;\n}\n"
    : "+f"(d[0]),"+f"(d[1]),"+f"(d[2]),"+f"(d[3]),"+f"(d[4]),"+f"(d[5]),"+f"(d[6]),"+f"(d[7]),"+f"(d[8]),"+f"(d[9]),"+f"(d[10]),"+f"(d[11]),"+f"(d[12]),"+f"(d[13]),"+f"(d[14]),"+f"(d[15]),"+f"(d[16]),"+f"(d[17]),"+f"(d[18]),"+f"(d[19]),"+f"(d[20]),"+f"(d[21]),"+f"(d[22]),"+f"(d[23]),"+f"(d[24]),"+f"(d[25]),"+f"(d[26]),"+f"(d[27]),"+f"(d[28]),"+f"(d[29]),"+f"(d[30]),"+f"(d[31])
    : "r"(al), "r"(bl), "n"(HA), "n"(HB));
}

__device__ __forceinline__ void mbar_init(uint32_t a, uint32_t c) { asm volatile("mbarrier.init.shared::cta.b64 [%0], %1;" ::"r"(a), "r"(c) : "memory"); }
__device__ __forceinline__ void mbar_expect(uint32_t a, uint32_t b) { asm volatile("mbarrier.arrive.expect_tx.shared::cta.b64 _, [%0], %1;" ::"r"(a), "r"(b) : "memory"); }
__device__ __forceinline__ void mbar_arrive(uint32_t a) { asm volatile("mbarrier.arrive.shared::cta.b64 _, [%0];" ::"r"(a) : "memory"); }
__device__ __forceinline__ void mbar_wait(uint32_t a) {
  asm volatile("{\n.reg .pred p;\n.reg .u32 n;\n"
               "mbarrier.try_wait.parity.shared::cta.b64 p, [%0], 0, 20000;\n@p bra LD;\nmov.u32 n, 0;\nLW:\n"
               "mbarrier.try_wait.parity.shared::cta.b64 p, [%0], 0, 20000;\n@p bra LD;\n"
               "add.u32 n, n, 1;\nsetp.lt.u32 p, n, 0x40000;\n@p bra LW;\ntrap;\nLD:\n}\n" ::"r"(a) : "memory");
}
__device__ __forceinline__ bool elect() {
  uint32_t r;
  asm volatile("{\n.reg .pred p;\nelect.sync _|p, 0xffffffff;\nselp.u32 %0, 1, 0, p;\n}\n" : "=r"(r));
  return r;
}
__device__ __forceinline__ void warp_arrive(uint32_t a) { __syncwarp(); if ((threadIdx.x & 31) == 0) mbar_arrive(a); }
__device__ __forceinline__ void tma2d(uint32_t dst, const CUtensorMap* m, int c0, int c1, uint32_t bar) {
  asm volatile("cp.async.bulk.tensor.2d.shared::cluster.global.mbarrier::complete_tx::bytes [%0], [%1, {%3, %4}], [%2];"
               ::"r"(dst), "l"(m), "r"(bar), "r"(c0), "r"(c1) : "memory");
}
__device__ __forceinline__ void bulk(uint32_t dst, const void* src, uint32_t bytes, uint32_t bar) {
  asm volatile("cp.async.bulk.shared::cluster.global.mbarrier::complete_tx::bytes [%0], [%1], %2, [%3];"
               ::"r"(dst), "l"(src), "r"(bytes), "r"(bar) : "memory");
}
__device__ __forceinline__ void signal(int c) { asm volatile("red.release.gpu.global.add.u32 [%0], 1;" ::"l"(&gCnt[c * 32]) : "memory"); }
__device__ __forceinline__ unsigned ld_epoch(int b) { unsigned v; asm volatile("ld.relaxed.gpu.global.u32 %0, [%1];" : "=r"(v) : "l"(&gEpoch[b]) : "memory"); return v + 1; }
template <int SLEEP> __device__ __forceinline__ void poll(int c, unsigned target) {
  for (int n = 0;; n++) {
    unsigned v;
    asm volatile("ld.acquire.gpu.global.u32 %0, [%1];" : "=r"(v) : "l"(&gCnt[c * 32]) : "memory");
    if ((int)(v - target) >= 0) break;
    if (n > (1 << 22)) __trap();
    if (SLEEP) __nanosleep(SLEEP);
  }
  asm volatile("fence.proxy.async.global;" ::: "memory");
}
__device__ __forceinline__ float ex2(float x) { float y; asm("ex2.approx.ftz.f32 %0, %1;" : "=f"(y) : "f"(x)); return y; }
__device__ __forceinline__ uint32_t pack(float lo, float hi) { uint32_t y; asm("cvt.rn.bf16x2.f32 %0, %1, %2;" : "=r"(y) : "f"(hi), "f"(lo)); return y; }
__device__ __forceinline__ void stg(uint8_t* p, uint32_t v) { asm volatile("st.global.u32 [%0], %1;" ::"l"(p), "r"(v) : "memory"); }
__device__ __forceinline__ uint32_t lds(uint32_t a) { uint32_t v; asm volatile("ld.shared.u32 %0, [%1];" : "=r"(v) : "r"(a) : "memory"); return v; }
__device__ __forceinline__ uint32_t hsq(uint32_t v, uint32_t a) { uint32_t y; asm("fma.rn.bf16x2 %0, %1, %1, %2;" : "=r"(y) : "r"(v), "r"(a)); return y; }
__device__ __forceinline__ float rownorm(uint4 a, uint4 b, uint4 c, uint2 d) {
  uint32_t x = hsq(a.x, hsq(a.y, hsq(a.z, hsq(a.w, hsq(b.x, hsq(b.y, hsq(d.x, 0)))))));
  uint32_t y = hsq(c.x, hsq(c.y, hsq(c.z, hsq(c.w, hsq(b.z, hsq(b.w, hsq(d.y, 0)))))));
  return (__uint_as_float(x << 16) + __uint_as_float(x & 0xFFFF0000u)) + (__uint_as_float(y << 16) + __uint_as_float(y & 0xFFFF0000u));
}
__device__ __forceinline__ uint32_t exp2_pair(float t0, float t1) {
  uint32_t w = __byte_perm(__float_as_uint(t0), __float_as_uint(t1), 0x6521);
  uint32_t m = w | 0x3F803F80u, g;
  asm("fma.rn.bf16x2 %0, %1, %1, %2;" : "=r"(g) : "r"(m), "r"(0x40014001u));
  return g + w - m;
}
__device__ __forceinline__ float phi(float t) { return (t > 0.f ? t + 1.f : ex2(t * 1.4426950408889634f)) + 1e-6f; }

constexpr uint32_t H_SW = (1024 >> 4) | (1u << 30);
constexpr uint32_t L_X = 1u << 16, L_W = (8192u >> 4) << 16;
constexpr uint32_t H_KM = 128 >> 4, L_KM = (2048u >> 4) << 16;
constexpr uint32_t H_MN = 2048 >> 4, L_MN = (128u >> 4) << 16;
constexpr uint32_t H_KV = 128 >> 4, L_KV = (512u >> 4) << 16;
constexpr uint32_t H_O = 128 >> 4, L_O = (1024u >> 4) << 16;

__device__ __forceinline__ void store_o(const float* o, float eps, uint8_t* base, bool odd, int lane) {
  const int src = (lane & 28) | (odd ? 0 : 2);
  const float r0 = __fdividef(1.f, __shfl_sync(~0u, odd ? o[0] : o[12], src) + eps);
  const float r1 = __fdividef(1.f, __shfl_sync(~0u, odd ? o[2] : o[14], src) + eps);
  const bool up = lane & 2;
#pragma unroll
  for (int c = 0; c < 4; c++) {
    if (c == 0 ? (!odd || up) : c == 3 ? (odd || !up) : true) {
      stg(base + c * 1024, pack(o[4 * c] * r0, o[4 * c + 1] * r0));
      stg(base + c * 1024 + 128, pack(o[4 * c + 2] * r1, o[4 * c + 3] * r1));
    }
  }
}

__device__ __forceinline__ void mma16816(float* d, uint32_t a0, uint32_t a1, uint32_t a2, uint32_t a3, uint32_t b0, uint32_t b1) {
  asm volatile("mma.sync.aligned.m16n8k16.row.col.f32.bf16.bf16.f32 {%0,%1,%2,%3}, {%4,%5,%6,%7}, {%8,%9}, {%0,%1,%2,%3};"
               : "+f"(d[0]), "+f"(d[1]), "+f"(d[2]), "+f"(d[3]) : "r"(a0), "r"(a1), "r"(a2), "r"(a3), "r"(b0), "r"(b1));
}
__device__ __forceinline__ void attn_safe(float* o, const uint8_t* qp, const uint8_t* kv, bool odd, int lane) {
  uint32_t q[8];
#pragma unroll
  for (int i = 0; i < 8; i++) q[i] = __ldcg((const uint32_t*)(qp + (i & 1) * 128 + (i >> 1) * 2048) + lane);
  if (!odd && (lane & 2)) q[6] = q[7] = 0;
  if (odd && !(lane & 2)) q[0] = q[1] = 0;
  float m0 = -INFINITY, m1 = -INFINITY;
#pragma unroll
  for (int i = 0; i < 16; i++) o[i] = 0.f;
#pragma unroll 1
  for (int it = 0; it < 128; it++) {
    const uint32_t* k = (const uint32_t*)(kv + (it >> 3) * M_STRIDE + (it & 7) * 256) + lane;
    uint32_t kb[8], vb[8];
#pragma unroll
    for (int i = 0; i < 8; i++) { kb[i] = __ldcg(k + (i >> 2) * 32 + (i & 3) * 512); vb[i] = __ldcg(k + SEC_STRIDE / 4 + (i >> 2) * 32 + (i & 3) * 512); }
    float s[8];
#pragma unroll
    for (int b = 0; b < 2; b++) {
      s[4 * b] = s[4 * b + 1] = s[4 * b + 2] = s[4 * b + 3] = 0.f;
      mma16816(s + 4 * b, q[0], q[1], q[2], q[3], kb[4 * b], kb[4 * b + 1]);
      mma16816(s + 4 * b, q[4], q[5], q[6], q[7], kb[4 * b + 2], kb[4 * b + 3]);
      const float f = ((EMU_MASK >> ((it & 7) * 2 + b)) & 1) ? 0.5f : 1.f;
#pragma unroll
      for (int i = 0; i < 4; i++) s[4 * b + i] *= f;
    }
    float n0 = fmaxf(fmaxf(s[0], s[1]), fmaxf(s[4], s[5])), n1 = fmaxf(fmaxf(s[2], s[3]), fmaxf(s[6], s[7]));
    n0 = fmaxf(n0, __shfl_xor_sync(~0u, n0, 1)); n1 = fmaxf(n1, __shfl_xor_sync(~0u, n1, 1));
    n0 = fmaxf(n0, __shfl_xor_sync(~0u, n0, 2)); n1 = fmaxf(n1, __shfl_xor_sync(~0u, n1, 2));
    n0 = fmaxf(n0, m0); n1 = fmaxf(n1, m1);
    const float a0 = ex2(m0 - n0), a1 = ex2(m1 - n1);
    m0 = n0; m1 = n1;
    const uint32_t p0 = pack(ex2(s[0] - m0), ex2(s[1] - m0)), p1 = pack(ex2(s[2] - m1), ex2(s[3] - m1));
    const uint32_t p2 = pack(ex2(s[4] - m0), ex2(s[5] - m0)), p3 = pack(ex2(s[6] - m1), ex2(s[7] - m1));
#pragma unroll
    for (int c = 0; c < 4; c++) {
      o[4 * c] *= a0; o[4 * c + 1] *= a0; o[4 * c + 2] *= a1; o[4 * c + 3] *= a1;
      uint32_t b0, b1;
      asm volatile("movmatrix.sync.aligned.m8n8.trans.b16 %0, %1;" : "=r"(b0) : "r"(vb[c]));
      asm volatile("movmatrix.sync.aligned.m8n8.trans.b16 %0, %1;" : "=r"(b1) : "r"(vb[4 + c]));
      mma16816(o + 4 * c, p0, p1, p2, p3, b0, b1);
    }
  }
}

__global__ void __launch_bounds__(NTHREADS, 1) fused_kernel(const __grid_constant__ Params P, __nv_bfloat16* __restrict__ out) {
  extern __shared__ __align__(1024) uint8_t smem_raw[];
  {
    const int t = threadIdx.x, br = t >= 192, i = blockIdx.x * 180 + t - br * 192;
    if (t < 372 && t - br * 192 < 180 && i < 23744) {
      const uint8_t* p = i < 9408 ? P.in[3 * br + 1] + i * 128 : P.in[3 * br] + (i - 9408) * 128;
      asm volatile("prefetch.global.L2 [%0];" ::"l"(p));
    }
  }
  const uint32_t sb = (uint32_t)__cvta_generic_to_shared(smem_raw);
  const uint32_t bar = sb + S_BAR;
  const uint32_t sd = (sb & 0x3FFFF) >> 4;
  const int bid = blockIdx.x, tid = threadIdx.x, lane = tid & 31;
  const int warp = __shfl_sync(~0u, tid >> 5, 0);
  const bool spare = bid >= 130 || bid == 112 || bid == 113;
  const int L = spare ? (bid >= 130 ? bid - 128 : bid - 112) : (bid < 112 ? bid : bid - 2);
  const int hi8 = L >> 3, lo8 = L & 7;
  const bool qcta = lo8 == 7;

  auto load_chunk = [&](int c, int job, int kc, int st) {
    const bool three = !spare && job == 0;
    const int br = (three && !qcta) ? 0 : 1, m = spare ? 4 * L + job : hi8;
    const int b0 = spare ? 5 : qcta ? 3 * job : 7 + lo8, b1 = (spare || qcta) ? b0 + 1 : b0 + 7;
    const uint32_t dst = sb + st * STAGE, fb = bar + 8 * (B_GF + c);
    mbar_expect(fb, three ? 40960 : 32768);
    tma2d(dst, &P.x[br], kc * 64, m * 128, fb);
    tma2d(dst + 16384, &P.w[br], b0 * 64, kc * 64, fb);
    tma2d(dst + 24576, &P.w[br], b1 * 64, kc * 64, fb);
    if (three) tma2d(dst + 32768, &P.w[br], (qcta ? 2 : lo8) * 64, kc * 64, fb);
  };
  if (elect()) {
    if (warp == 16) {
      mbar_init(bar, 1);
      load_chunk(0, 0, 0, 1);
      STAMP(44);
    } else {
#pragma unroll 1
      for (int i = warp < 16 ? warp + 1 : warp; i < B_END; i += 19) {
        uint32_t cnt = 1;
        if (i >= B_GE && i < B_KF) cnt = (!spare && i < B_GE + 7) ? 16 : 8;
        if ((i >= B_KE && i < B_OF) || i == B_XFREE || i == B_SOB) cnt = 16;
        if ((i >= B_OE && i < B_QF) || i == B_SKV) cnt = 4;
        if ((i >= B_SG && i < B_SKV) || i == B_SOA) cnt = (!spare && i == B_SG) ? 16 : 8;
        mbar_init(bar + 8 * i, cnt);
      }
    }
  }
  __syncthreads();
  if (warp == 16) STAMP(43);

  if (warp >= 16) {
    asm volatile("setmaxnreg.dec.sync.aligned.u32 32;");
    const int h = hi8, qb = lo8;
    const int m64 = (hi8 >> 1) * 4 + (hi8 & 1);
    auto o_slot = [&](int kc) { return sb + (kc < 2 ? S_RING + (4 + kc) * 16384 : kc < 6 ? S_RING + (kc - 2) * 16384 : S_Q); };
    auto load_oa = [&](int w, unsigned ep) {
      poll<0>(C_OA + m64 + 2 * w, ep * 64);
      STAMP(34 + w);
#pragma unroll 1
      for (int kc = 0; kc < 7; kc++) {
        mbar_wait(bar + 8 * (B_OE + 7 * w + kc));
        mbar_expect(bar + 8 * (B_OF + 7 + 7 * w + kc), 8192);
        bulk(o_slot(kc) + w * 8192, gO[0] + (m64 + 2 * w) * 57344 + kc * 8192, 8192, bar + 8 * (B_OF + 7 + 7 * w + kc));
      }
    };
    if (warp == 16) {
      if (elect()) {
        const int nchunk = spare ? 28 : 14;
        int st = 2, kc = 1, job = 0;
        unsigned ep = 0;
#pragma unroll 1
        for (int c = 1; c < nchunk; c++) {
          if (c == 5) { STAMP(45); ep = ld_epoch(bid); }
          if (c >= 5) mbar_wait(bar + 8 * (B_GE + c - 5));
          load_chunk(c, job, kc, st);
          st = st == 4 ? 0 : st + 1;
          if (++kc == 7) { kc = 0; job++; }
        }
        STAMP(32);
        if (!spare) {
          poll<0>(C_A + (h >> 1), ep * 16);
          poll<0>(C_A + (28 * h >> 6), ep * 16);
          poll<0>(C_A + ((28 * h + 27) >> 6), ep * 16);
          STAMP(33);
          const uint8_t* src = gQKV[0] + h * 8192;
          mbar_expect(bar + 8 * B_QF, 16384);
          bulk(sb + S_Q, src + (2 * qb) * M_STRIDE, 8192, bar + 8 * B_QF);
          bulk(sb + S_Q + 8192, src + (2 * qb + 1) * M_STRIDE, 8192, bar + 8 * B_QF);
          int slot = 0;
#pragma unroll 1
          for (int t = 0; t < 16; t++) {
            mbar_wait(bar + 8 * (t >= 6 ? B_KE + t - 6 : B_GE + (t < 2 ? 9 : t < 5 ? 10 : 11)));
            mbar_expect(bar + 8 * (B_KF + t), 16384);
            bulk(sb + S_RING + slot * 16384, src + t * M_STRIDE + SEC_STRIDE, 8192, bar + 8 * (B_KF + t));
            bulk(sb + S_RING + slot * 16384 + 8192, src + t * M_STRIDE + 2 * SEC_STRIDE, 8192, bar + 8 * (B_KF + t));
            slot = slot == 5 ? 0 : slot + 1;
          }
          poll<100>(C_OB + (hi8 >> 1), ep * 16);
          mbar_wait(bar + 8 * B_GUARD);
#pragma unroll 1
          for (int kc = 0; kc < 7; kc++) {
            mbar_wait(bar + 8 * (B_KE + (kc < 6 ? 10 + kc : 15)));
            mbar_expect(bar + 8 * (B_OF + kc), 16384);
            bulk(o_slot(kc), gO[1] + m64 * 57344 + kc * 8192, 8192, bar + 8 * (B_OF + kc));
            bulk(o_slot(kc) + 8192, gO[1] + (m64 + 2) * 57344 + kc * 8192, 8192, bar + 8 * (B_OF + kc));
          }
        }
      }
    } else if (spare) {
      if (warp == 19 && elect()) {
        for (int j = 0; j < 4; j++) { mbar_wait(bar + 8 * (B_SG + j)); signal(C_BQ + 2 * L + (j >> 1)); }
      }
    } else if (warp == 17) {
      const unsigned ep = ld_epoch(bid);
      const uint8_t* src = gQKV[1] + h * 8192 + 2 * qb * M_STRIDE;
      if (elect()) {
        mbar_wait(bar + 8 * (B_KF + 2));
        poll<100>(C_BK + qb, ep * 14);
        mbar_wait(bar + 8 * (B_GE + 13));
        mbar_expect(bar + 8 * B_PKV, 32768);
#pragma unroll
        for (int i = 0; i < 4; i++) bulk(sb + S_PKV + i * 8192, src + (i >> 1) * M_STRIDE + (1 + (i & 1)) * SEC_STRIDE, 8192, bar + 8 * B_PKV);
        STAMP(36);
        mbar_wait(bar + 8 * (B_KE + 1));
        mbar_expect(bar + 8 * B_WOB, 57344);
        tma2d(sb + S_WOB, &P.wo[1], lo8 * 56, 0, bar + 8 * B_WOB);
        tma2d(sb + S_WOB + 28672, &P.wo[1], lo8 * 56, 224, bar + 8 * B_WOB);
        mbar_wait(bar + 8 * B_SKV);
        poll<100>(C_KV + h, ep * 8);
        mbar_expect(bar + 8 * B_PART, 32768);
        bulk(sb + S_PKV, gPart + h * 8192, 32768, bar + 8 * B_PART);
        STAMP(37);
      }
      __syncwarp();
      mbar_wait(bar + 8 * B_PART);
#pragma unroll 1
      for (int it = 0; it < 8; it++) {
        float4 a = *(const float4*)(smem_raw + S_PKV + it * 512 + lane * 16);
#pragma unroll
        for (int p = 1; p < 8; p++) {
          float4 v = *(const float4*)(smem_raw + S_PKV + p * 4096 + it * 512 + lane * 16);
          a.x += v.x; a.y += v.y; a.z += v.z; a.w += v.w;
        }
        *(uint2*)(smem_raw + S_KVM + it * 256 + lane * 8) = make_uint2(pack(a.x, a.y), pack(a.z, a.w));
      }
      asm volatile("fence.proxy.async.shared::cta;" ::: "memory");
      __syncwarp();
      if (elect()) {
        mbar_arrive(bar + 8 * B_KVM);
        STAMP(40);
        poll<100>(C_BQ + qb, ep * 6);
        mbar_expect(bar + 8 * B_PQ, 16384);
        bulk(sb + S_PQ, src, 8192, bar + 8 * B_PQ);
        bulk(sb + S_PQ + 8192, src + M_STRIDE, 8192, bar + 8 * B_PQ);
        STAMP(38);
        mbar_wait(bar + 8 * B_XFREE);
        mbar_expect(bar + 8 * B_WOA, 57344);
        tma2d(sb + S_WOA, &P.wo[0], lo8 * 56, 0, bar + 8 * B_WOA);
        tma2d(sb + S_WOA + 28672, &P.wo[0], lo8 * 56, 224, bar + 8 * B_WOA);
        mbar_wait(bar + 8 * (B_KE + 14));
        load_oa(0, ep);
      }
    } else if (warp == 18) {
      const unsigned ep = ld_epoch(bid);
      mbar_wait(bar + 8 * B_QF);
      const uint32_t o3 = (h & 1) * 2048 + lane * 16, o1 = ((h & 1) ? 8 : 6144) + lane * 16;
      uint32_t kmax = 0, qmax = 0;
#pragma unroll 1
      for (int u = 0; u < 8; u++) {
        const uint8_t* p = gQKV[0] + h * 8192 + (2 * qb + (u >> 2)) * M_STRIDE + SEC_STRIDE + (u & 3) * 512;
        float a = rownorm(__ldcg((const uint4*)(p + o3)), __ldcg((const uint4*)(p + o3 + 2048)), __ldcg((const uint4*)(p + o3 + 4096)), __ldcg((const uint2*)(p + o1)));
        if ((EMU_MASK >> ((u & 3) * 4 + (lane >> 3))) & 1) a *= 0.25f;
        kmax = max(kmax, __float_as_uint(a) & 0x7FFFFFFFu);
      }
      kmax = __reduce_max_sync(~0u, kmax);
      if (lane == 0) asm volatile("st.relaxed.gpu.global.u64 [%0], %1;" ::"l"(&gKn[L]), "l"(((unsigned long long)ep << 32) | kmax) : "memory");
#pragma unroll 1
      for (int u = 0; u < 8; u++) {
        const uint8_t* p = smem_raw + S_Q + (u >> 2) * 8192 + (u & 3) * 512;
        float a = rownorm(*(const uint4*)(p + o3), *(const uint4*)(p + o3 + 2048), *(const uint4*)(p + o3 + 4096), *(const uint2*)(p + o1));
        qmax = max(qmax, __float_as_uint(a) & 0x7FFFFFFFu);
      }
      qmax = __reduce_max_sync(~0u, qmax);
      unsigned long long v;
      for (int n = 0;; n++) {
        asm volatile("ld.relaxed.gpu.global.u64 %0, [%1];" : "=l"(v) : "l"(&gKn[h * 8 + (lane & 7)]) : "memory");
        if (__all_sync(~0u, (unsigned)(v >> 32) == ep)) break;
        if (n > (1 << 22)) __trap();
        __nanosleep(100);
      }
      kmax = __reduce_max_sync(~0u, (unsigned)v);
      asm volatile("fence.proxy.async.shared::cta;" ::: "memory");
      __syncwarp();
      if (elect()) {
        *(volatile uint32_t*)(smem_raw + S_MISC) = (__uint_as_float(qmax) * __uint_as_float(kmax) <= GUARD) ? 0u : 1u;
        mbar_arrive(bar + 8 * B_GUARD);
        STAMP(39);
        mbar_wait(bar + 8 * (B_KE + 15));
        load_oa(1, ep);
      }
    } else if (elect()) {
      mbar_wait(bar + 8 * B_SG); signal(C_A + lo8);
      if (qcta) signal(C_BQ + (hi8 >> 1));
      STAMP(41);
      mbar_wait(bar + 8 * (B_SG + 1)); signal((qcta ? C_BQ : C_BK) + (hi8 >> 1));
      STAMP(42);
      mbar_wait(bar + 8 * B_SKV); signal(C_KV + h);
      mbar_wait(bar + 8 * B_SOB); signal(C_OB + qb);
      mbar_wait(bar + 8 * B_SOA);
      asm volatile("fence.acq_rel.gpu;\nred.relaxed.gpu.global.add.u32 [%0], 4;\nred.relaxed.gpu.global.add.u32 [%0+128], 4;"
                   ::"l"(&gCnt[(C_OA + qb * 4) * 32]) : "memory");
    }
  } else {
    asm volatile("setmaxnreg.inc.sync.aligned.u32 112;");
    const int wg = warp >> 2, ww = warp & 3, pair = wg >> 1, w = wg & 1;
    {
      float acc[64];
      const int njob = (spare || pair) ? 2 : 1;
      const int up = (lane >> 1) & 1, rg = 8 * w + 2 * ww;
      const bool e0 = (EMU_MASK >> rg) & 1, e1 = (EMU_MASK >> (rg + 1)) & 1;
      if (!spare) {
        uint8_t* pp = gQKV[pair] + hi8 * M_STRIDE + (8 * lo8 + 4 - up) * 2048 + rg * 128 + lane * 4;
        const bool o = lane & 1;
        const uint32_t pq = pair ? 0u : o ? 0x00003F80u : 0x3F803F80u, pv = o ? 0u : 0x00003F80u;
        const uint32_t pe = pair ? 0u : o ? 0x00003C3Cu : 0x40344426u, pm = (pair || o) ? 0u : 0x0000C240u;
        stg(pp, pq); stg(pp + 128, pq);
        stg(pp + SEC_STRIDE, e0 ? pe : pm); stg(pp + SEC_STRIDE + 128, e1 ? pe : pm);
        stg(pp + 2 * SEC_STRIDE, pv); stg(pp + 2 * SEC_STRIDE + 128, pv);
      }
#pragma unroll 1
      for (int jb = 0; jb < njob; jb++) {
        const int job = spare ? pair + 2 * jb : jb;
        const bool n64 = !spare && pair && jb == 0;
        const int br = (!spare && job == 0 && !qcta) ? 0 : 1, m = spare ? 4 * L + job : hi8;
        const int c0 = job * 7;
        int st = (c0 + 1) % 5;
#pragma unroll
        for (int i = 0; i < 64; i++) acc[i] = 0.f;
        pin<64>(acc);
        if (n64) {
#pragma unroll 1
          for (int kc = 0; kc < 7; kc++) {
            mbar_wait(bar + 8 * (B_GF + c0 + kc));
            const uint32_t a = (sd + st * (STAGE >> 4) + w * 512) | L_X, b = (sd + st * (STAGE >> 4) + 2048) | L_W;
            wg_fence();
#pragma unroll
            for (int k = 0; k < 4; k++) wg64_ss_tb<H_SW, H_SW>(acc, a + 2 * k, b + 128 * k);
            wg_commit();
            wg_wait<1>();
            if (kc > 0 && lane == 0) mbar_arrive(bar + 8 * (B_GE + c0 + kc - 1));
            st = st == 4 ? 0 : st + 1;
          }
          wg_wait<0>();
        } else {
#pragma unroll 1
          for (int kc = 0; kc < 7; kc++) {
            mbar_wait(bar + 8 * (B_GF + c0 + kc));
            if (kc == 0) STAMP(wg * 8 + 0);
            const uint32_t a = (sd + st * (STAGE >> 4) + w * 512) | L_X, b = (sd + st * (STAGE >> 4) + 1024) | L_W;
            wg_fence();
#pragma unroll
            for (int k = 0; k < 4; k++) wg128_ss_tb<H_SW, H_SW>(acc, a + 2 * k, b + 128 * k);
            wg_commit();
            wg_wait<1>();
            if (kc > 0 && lane == 0) mbar_arrive(bar + 8 * (B_GE + c0 + kc - 1));
            st = st == 4 ? 0 : st + 1;
          }
          wg_wait<0>();
        }
        pin<64>(acc);
        if (lane == 0) mbar_arrive(bar + 8 * (B_GE + c0 + 6));
        STAMP(wg * 8 + 1);
        int box = n64 ? (qcta ? 2 : lo8) : spare ? 5 : qcta ? 3 * job : 7 + lo8;
        const int nb = n64 ? 1 : 2;
#pragma unroll 1
        for (int b = 0; b < nb; b++) {
          const int sec = box >= 14 ? 2 : box >= 7 ? 1 : 0, j = box - 7 * sec;
          uint32_t pk[16];
          if (br == 1 && sec < 2) {
#pragma unroll
            for (int i = 0; i < 16; i++) pk[i] = pack(phi(acc[2 * i]), phi(acc[2 * i + 1]));
          } else {
            const float f0 = sec == 0 ? 0.27264374f : (sec == 1 && e0) ? 2.f : 1.f;
            const float f1 = sec == 0 ? 0.27264374f : (sec == 1 && e1) ? 2.f : 1.f;
#pragma unroll
            for (int i = 0; i < 8; i++) {
              pk[2 * i] = pack(acc[4 * i] * f0, acc[4 * i + 1] * f0);
              pk[2 * i + 1] = pack(acc[4 * i + 2] * f1, acc[4 * i + 3] * f1);
            }
          }
          uint8_t* base = gQKV[br] + m * M_STRIDE + sec * SEC_STRIDE + rg * 128 + lane * 4;
          const int u = j + 3 + up, thr = u >= 7 ? 14 - u : 7 - u;
          uint8_t* pa = base + (9 * j + (u >= 7)) * 2048;
          uint8_t* pb = pa + 2048;
#pragma unroll
          for (int i = 0; i < 8; i++) {
            uint8_t* p = (i >= thr ? pb : pa) + i * 2048;
            stg(p, pk[2 * i]); stg(p + 128, pk[2 * i + 1]);
          }
#pragma unroll
          for (int i = 0; i < 32; i++) acc[i] = acc[32 + i];
          box += (spare || qcta) ? 1 : 7;
        }
        warp_arrive(bar + 8 * (B_SG + job));
        STAMP(wg * 8 + 2);
      }
    }
    if (!spare) {
      const int h = hi8, qb = lo8;
      const bool odd = h & 1;
      uint8_t* obase = gO[0] + (qb * 4 + wg) * 57344 + (7 * (h >> 1) + 3 * (h & 1)) * 1024 + ww * 256 + lane * 4;
      float o[16];
      {
        float s[64];
        uint32_t p[32];
#pragma unroll
        for (int i = 0; i < 16; i++) o[i] = 0.f;
        pin<16>(o);
        const uint32_t k0 = odd ? 256 : 0, k1 = 256 - k0;
        const uint32_t dq = (sd + (S_Q >> 4) + pair * 512 + w * 64) | L_KM;
        mbar_wait(bar + 8 * B_QF);
        uint32_t cur = sd;
#pragma unroll 1
        for (int t = 0; t < 16; t++) {
          mbar_wait(bar + 8 * (B_KF + t));
          if (t == 0) STAMP(wg * 8 + 3);
          if (wg == 1 && t > 0) STAMP(46 + t);
          wg_fence();
          wg128_ss_z<H_KM, H_KM>(s, dq + k0, (cur | L_KM) + k0);
          wg128_ss<H_KM, H_KM>(s, dq + k1, (cur | L_KM) + k1);
          wg_commit();
          wg_wait<0>();
          pin<64>(s);
#pragma unroll
          for (int g = 0; g < 16; g++) {
            if ((EMU_MASK >> g) & 1) {
              p[2 * g] = exp2_pair(s[4 * g], s[4 * g + 1]);
              p[2 * g + 1] = exp2_pair(s[4 * g + 2], s[4 * g + 3]);
            } else {
              p[2 * g] = pack(ex2(s[4 * g]), ex2(s[4 * g + 1]));
              p[2 * g + 1] = pack(ex2(s[4 * g + 2]), ex2(s[4 * g + 3]));
            }
          }
          pin<32>(p);
          wg_fence();
#pragma unroll
          for (int k = 0; k < 8; k++) wg32_rs_tb<H_MN>(o, p[4 * k], p[4 * k + 1], p[4 * k + 2], p[4 * k + 3], ((cur + 512) | L_MN) + 16 * k);
          wg_commit();
          wg_wait<0>();
          pin<16>(o);
          if (lane == 0) mbar_arrive(bar + 8 * (B_KE + t));
          cur = cur == sd + 5 * 1024 ? sd : cur + 1024;
          if (t == T_KVP && wg == 0) {
            mbar_wait(bar + 8 * B_PKV);
            const uint32_t a = (sd + (S_PKV >> 4)) | L_MN;
            wg_fence();
            wg32_ss_ta_tb_z<H_MN, H_MN>(s, a, a + 512);
#pragma unroll
            for (int k = 1; k < 16; k++) wg32_ss_ta_tb<H_MN, H_MN>(s, a + (k >> 3) * 1024 + (k & 7) * 16, a + 512 + (k >> 3) * 1024 + (k & 7) * 16);
            wg_commit();
            wg_wait<0>();
            pin<16>(s);
            if (ww < 2) {
              float2* dst = (float2*)gPart + L * 512 + ww * 256 + lane;
#pragma unroll
              for (int c = 0; c < 4; c++) {
                dst[c * 32] = make_float2(s[4 * c], s[4 * c + 1]);
                dst[128 + c * 32] = make_float2(s[4 * c + 2], s[4 * c + 3]);
              }
            }
            warp_arrive(bar + 8 * B_SKV);
          }
          if (t == T_OB) {
            mbar_wait(bar + 8 * B_KVM);
            mbar_wait(bar + 8 * B_PQ);
            const uint32_t a = (sd + (S_PQ >> 4) + pair * 512 + w * 64) | L_KM, b = (sd + (S_KVM >> 4)) | L_KV;
            wg_fence();
            wg32_ss_tb_z<H_KM, H_KV>(s, a, b);
            wg32_ss_tb<H_KM, H_KV>(s, a + 256, b + 64);
            wg_commit();
            wg_wait<0>();
            pin<16>(s);
            if (lane == 0) mbar_arrive(bar + 8 * B_XFREE);
            store_o(s, 1e-6f, obase + sizeof(gO[0]), odd, lane);
            warp_arrive(bar + 8 * B_SOB);
          }
        }
      }
      STAMP(wg * 8 + 4);
      mbar_wait(bar + 8 * B_GUARD);
      {
        float a0 = 0.f, a1 = 0.f;
#pragma unroll
        for (int c = 1; c < 3; c++) {
          a0 = fmaxf(a0, fmaxf(fabsf(o[4 * c]), fabsf(o[4 * c + 1])));
          a1 = fmaxf(a1, fmaxf(fabsf(o[4 * c + 2]), fabsf(o[4 * c + 3])));
        }
        const bool bad = lds(sb + S_MISC) != 0 || fminf(a0, a1) < 7.888609e-31f;
        if (__any_sync(~0u, bad))
          attn_safe(o, gQKV[0] + h * 8192 + (2 * qb + pair) * M_STRIDE + w * 1024 + ww * 256, gQKV[0] + h * 8192 + SEC_STRIDE, odd, lane);
      }
      store_o(o, 0.f, obase, odd, lane);
      __syncwarp();
      if (lane == 0) { if (pair) signal(C_OA + qb * 4 + wg); else mbar_arrive(bar + 8 * B_SOA); }
      STAMP(wg * 8 + 5);
      float acc[28];
#pragma unroll
      for (int i = 0; i < 28; i++) acc[i] = 0.f;
      pin<28>(acc);
      mbar_wait(bar + 8 * (pair ? B_WOA : B_WOB));
      const uint32_t wo = (sd + ((pair ? S_WOA : S_WOB) >> 4)) | L_W;
      const uint32_t fb = bar + 8 * (B_OF + (pair ? 7 + 7 * w : 0)), eb = bar + 8 * (B_OE + 7 * w);
#pragma unroll 1
      for (int kc = 0; kc < 7; kc++) {
        mbar_wait(fb + 8 * kc);
        const uint32_t a = (sd + (kc < 2 ? (4 + kc) * 1024 : kc < 6 ? (kc - 2) * 1024 : (S_Q >> 4)) + w * 512) | L_O;
        wg_fence();
#pragma unroll
        for (int k = 0; k < 4; k++) wg56_ss_tb<H_O, H_SW>(acc, a + 128 * k, wo + kc * 512 + 128 * k);
        wg_commit();
        wg_wait<1>();
        if (kc > 0 && !pair && lane == 0) mbar_arrive(eb + 8 * (kc - 1));
      }
      wg_wait<0>();
      pin<28>(acc);
      STAMP(wg * 8 + 6);
      asm volatile("bar.sync %0, 128;" ::"r"(1 + wg) : "memory");
      const uint32_t stg_s = sb + S_Q + w * 8192 + ww * 1792;
#pragma unroll
      for (int b = 0; b < 4; b++) {
        const uint32_t a = stg_s + (lane & 15) * 112 + (lane >> 4) * 16 + b * 32;
        if (b < 3)
          asm volatile("stmatrix.sync.aligned.m8n8.x4.shared.b16 [%0], {%1,%2,%3,%4};" ::"r"(a), "r"(pack(acc[8 * b], acc[8 * b + 1])),
                       "r"(pack(acc[8 * b + 2], acc[8 * b + 3])), "r"(pack(acc[8 * b + 4], acc[8 * b + 5])), "r"(pack(acc[8 * b + 6], acc[8 * b + 7])) : "memory");
        else
          asm volatile("stmatrix.sync.aligned.m8n8.x2.shared.b16 [%0], {%1,%2};" ::"r"(a), "r"(pack(acc[24], acc[25])), "r"(pack(acc[26], acc[27])) : "memory");
      }
      __syncwarp();
      uint8_t* dst = (uint8_t*)out + (((hi8 >> 1) * 4 + (hi8 & 1) + 2 * w) * 64 + ww * 16) * 1792 + (pair ? 0 : 896) + lo8 * 112;
#pragma unroll
      for (int i = 0; i < 4; i++) {
        const int e = i * 32 + lane, r = (e * 147) >> 10;
        if (i < 3 || lane < 16) {
          uint4 v;
          asm volatile("ld.shared.v4.u32 {%0,%1,%2,%3}, [%4];" : "=r"(v.x), "=r"(v.y), "=r"(v.z), "=r"(v.w) : "r"(stg_s + e * 16) : "memory");
          *(uint4*)(dst + r * (1792 - 112) + e * 16) = v;
        }
      }
      if (!pair) { asm volatile("fence.proxy.async.shared::cta;" ::: "memory"); warp_arrive(eb + 8 * 6); }
      if (tid == 384) atomicAdd(&gEpoch[bid], 1u);
      STAMP(wg * 8 + 7);
    }
  }
}

typedef CUresult (*EncodeFn)(CUtensorMap*, CUtensorMapDataType, cuuint32_t, void*, const cuuint64_t*, const cuuint64_t*,
                             const cuuint32_t*, const cuuint32_t*, CUtensorMapInterleave, CUtensorMapSwizzle,
                             CUtensorMapL2promotion, CUtensorMapFloatOOBfill);
void make_map(EncodeFn f, CUtensorMap* m, void* p, uint64_t cols, uint64_t rows, uint32_t box_rows) {
  cuuint64_t gd[2] = {cols, rows}, gs[1] = {cols * 2};
  cuuint32_t bd[2] = {64, box_rows}, es[2] = {1, 1};
  f(m, CU_TENSOR_MAP_DATA_TYPE_BFLOAT16, 2, p, gd, gs, bd, es, CU_TENSOR_MAP_INTERLEAVE_NONE, CU_TENSOR_MAP_SWIZZLE_128B,
    CU_TENSOR_MAP_L2_PROMOTION_NONE, CU_TENSOR_MAP_FLOAT_OOB_FILL_NONE);
}

}

extern "C" void kernel_launch(void* const* d_in, const int* in_sizes, int n_in, void* d_out, int out_size) {
  static EncodeFn enc = nullptr;
  if (!enc) {
    void* fn = nullptr;
    cudaDriverEntryPointQueryResult q;
    cudaGetDriverEntryPoint("cuTensorMapEncodeTiled", &fn, cudaEnableDefault, &q);
    enc = (EncodeFn)fn;
    cudaFuncSetAttribute(fused_kernel, cudaFuncAttributeMaxDynamicSharedMemorySize, SMEM_BYTES);
  }
  Params P;
  for (int i = 0; i < 6; i++) P.in[i] = (const uint8_t*)d_in[i];
  for (int b = 0; b < 2; b++) {
    make_map(enc, &P.x[b], d_in[3 * b], 448, 2048, 128);
    make_map(enc, &P.w[b], d_in[3 * b + 1], 1344, 448, 64);
    make_map(enc, &P.wo[b], d_in[3 * b + 2], 448, 448, 224);
  }
  fused_kernel<<<NCTA, NTHREADS, SMEM_BYTES>>>(P, (__nv_bfloat16*)d_out);
}
```

```cpp
#include <cuda_runtime.h>
#include <cuda.h>
#include <cuda_bf16.h>
#include <stddef.h>
#include <stdint.h>

namespace {

constexpr int NTHREADS = 640, NCTA = 132;

constexpr uint32_t M_STRIDE = 393216, SEC_STRIDE = 131072;
struct __align__(1024) Scratch {
  uint8_t qkv[2][16 * M_STRIDE];
  uint8_t o[2][32 * 57344];
  float part[16 * 8 * 1024];
  unsigned cnt[96 * 32];
  uint2 nrm[2][16][64];
  unsigned epoch[NCTA];
};
__device__ Scratch gScratch;
constexpr int C_A = 0, C_BK = 8, C_BQ = 16, C_OB = 24, C_KV = 32, C_OA = 48;

constexpr uint32_t SB = 1024;
constexpr uint32_t S_X = SB, S_W0 = SB + 114688, S_W1 = SB + 172032;
__host__ __device__ constexpr uint64_t slots(int a, int b, int c, int d, int e, int f, int g) {
  return a | b << 8 | c << 16 | (uint64_t)d << 24 | (uint64_t)e << 32 | (uint64_t)f << 40 | (uint64_t)g << 48;
}
constexpr uint64_t T_X = slots(0, 2, 4, 6, 8, 10, 12), T_W0 = slots(14, 15, 16, 17, 18, 19, 20), T_W1 = slots(21, 22, 23, 24, 25, 26, 27),
                   T_XB = slots(22, 24, 0, 2, 4, 6, 8), T_W3 = slots(21, 26, 27, 14, 15, 16, 17),
                   T_W4 = slots(18, 10, 11, 19, 12, 13, 20), T_W4Q = slots(22, 23, 24, 25, 18, 19, 20);
__host__ __device__ constexpr uint32_t slot(uint64_t t, int kc) { return SB + (uint32_t)((t >> (8 * kc)) & 31) * 8192; }
constexpr uint32_t S_WOB = SB, S_WOA = SB + 57344, S_R0 = S_W0, S_R1 = S_W0 + 16384, S_EXT = S_W0 + 32768,
                   S_R2 = S_W1 + 8192, S_R3 = S_W1 + 24576, S_Q = S_W1 + 40960;
constexpr uint32_t S_PKV = S_WOA, S_PQ = S_WOA + 32768, S_KVM = S_WOA + 49152;
constexpr uint32_t S_STG = S_WOB;
constexpr uint32_t S_BAR = SB + 229376, S_MISC = S_BAR + 2048;
constexpr uint32_t SMEM_BYTES = S_MISC + 512 - SB;
__host__ __device__ constexpr uint32_t ring_slot(int u) { return u == 0 ? S_R0 : u == 1 ? S_R1 : u == 2 ? S_R2 : S_R3; }
__host__ __device__ constexpr uint32_t ob_slot(int kc, int w) {
  return kc == 6 ? (w ? S_R3 : S_WOA + 49152) : (kc < 2 ? S_EXT + kc * 16384 : kc < 5 ? ring_slot(kc - 2) : S_WOA + 32768) + w * 8192;
}
__host__ __device__ constexpr uint32_t oa_slot(int kc, int w) { return kc == 0 ? (w ? S_Q : S_R3) + 8192 : ob_slot(kc - 1, w); }
__host__ __device__ constexpr uint32_t woa_slot(int kc) { return kc < 4 ? S_WOA + kc * 8192 : S_WOB + (kc - 4) * 8192; }
constexpr int B_F = 0  , B_KF = 35  , B_QF = 51  , B_OF = 53  , B_PKV = 74, B_STGF = 75, B_PART = 76,
              B_ASIG = 77, B_WOB = 78, B_WOA = 79,
              B_SG = 80  , B_QD = 85  , B_E = 88  , B_OE = 123  , B_SKV = 137, B_OGO = 138, B_QD3 = 139, B_QFREE = 140, B_OBGO = 141,
              B_PAD = 142, B_ASEQ = 143,
              B_KE = 144  , B_SOB = 161, B_DONE = 162,
              B_WOA2 = 164, B_AISS = 165;
__host__ __device__ constexpr uint32_t BAR(int i) { return S_BAR + 8 * i; }

constexpr uint32_t EMU_MASK = 0xF9B6;
constexpr int T_KV = 4;
constexpr int T_OB = 10;
constexpr float QSCALE = 0.27264374f;
constexpr float GUARD = 56.0f * 56.0f;

struct Params { CUtensorMap x[2], w[2], wo[2]; };

__device__ __forceinline__ void wg_fence() { asm volatile("wgmma.fence.sync.aligned;" ::: "memory"); }
__device__ __forceinline__ void wg_commit() { asm volatile("wgmma.commit_group.sync.aligned;" ::: "memory"); }
template <int N> __device__ __forceinline__ void wg_wait() { asm volatile("wgmma.wait_group.sync.aligned %0;" ::"n"(N) : "memory"); }
template <int M, int N> __device__ __forceinline__ void pin(float (&d)[N]) {
#pragma unroll
  for (int i = 0; i < M; i++) asm volatile("" : "+f"(d[i])::"memory");
}
template <int M, int N> __device__ __forceinline__ void pin(uint32_t (&d)[N]) {
#pragma unroll
  for (int i = 0; i < M; i++) asm volatile("" : "+r"(d[i])::"memory");
}
template<uint32_t HA, uint32_t HB, int NN> __device__ __forceinline__ void wg128_ss_ta(float (&d)[NN], uint32_t al, uint32_t bl) {
  asm volatile("{\n.reg .pred p;\n.reg .b64 da, db;\nsetp.ne.b32 p, 1, 0;\nmov.b64 da, {%64, %66};\nmov.b64 db, {%65, %67};\n"
    "wgmma.mma_async.sync.aligned.m64n128k16.f32.bf16.bf16 {%0,%1,%2,%3,%4,%5,%6,%7,%8,%9,%10,%11,%12,%13,%14,%15,%16,%17,%18,%19,%20,%21,%22,%23,%24,%25,%26,%27,%28,%29,%30,%31,%32,%33,%34,%35,%36,%37,%38,%39,%40,%41,%42,%43,%44,%45,%46,%47,%48,%49,%50,%51,%52,%53,%54,%55,%56,%57,%58,%59,%60,%61,%62,%63}, da, db, p, 1, 1, 1, 0;\n}\n"
    : "+f"(d[0]),"+f"(d[1]),"+f"(d[2]),"+f"(d[3]),"+f"(d[4]),"+f"(d[5]),"+f"(d[6]),"+f"(d[7]),"+f"(d[8]),"+f"(d[9]),"+f"(d[10]),"+f"(d[11]),"+f"(d[12]),"+f"(d[13]),"+f"(d[14]),"+f"(d[15]),"+f"(d[16]),"+f"(d[17]),"+f"(d[18]),"+f"(d[19]),"+f"(d[20]),"+f"(d[21]),"+f"(d[22]),"+f"(d[23]),"+f"(d[24]),"+f"(d[25]),"+f"(d[26]),"+f"(d[27]),"+f"(d[28]),"+f"(d[29]),"+f"(d[30]),"+f"(d[31]),"+f"(d[32]),"+f"(d[33]),"+f"(d[34]),"+f"(d[35]),"+f"(d[36]),"+f"(d[37]),"+f"(d[38]),"+f"(d[39]),"+f"(d[40]),"+f"(d[41]),"+f"(d[42]),"+f"(d[43]),"+f"(d[44]),"+f"(d[45]),"+f"(d[46]),"+f"(d[47]),"+f"(d[48]),"+f"(d[49]),"+f"(d[50]),"+f"(d[51]),"+f"(d[52]),"+f"(d[53]),"+f"(d[54]),"+f"(d[55]),"+f"(d[56]),"+f"(d[57]),"+f"(d[58]),"+f"(d[59]),"+f"(d[60]),"+f"(d[61]),"+f"(d[62]),"+f"(d[63])
    : "r"(al), "r"(bl), "n"(HA), "n"(HB));
}
template<uint32_t HA, uint32_t HB, int NN> __device__ __forceinline__ void wg128_ss_ta_z(float (&d)[NN], uint32_t al, uint32_t bl) {
  asm volatile("{\n.reg .pred p;\n.reg .b64 da, db;\nsetp.ne.b32 p, 0, 0;\nmov.b64 da, {%64, %66};\nmov.b64 db, {%65, %67};\n"
    "wgmma.mma_async.sync.aligned.m64n128k16.f32.bf16.bf16 {%0,%1,%2,%3,%4,%5,%6,%7,%8,%9,%10,%11,%12,%13,%14,%15,%16,%17,%18,%19,%20,%21,%22,%23,%24,%25,%26,%27,%28,%29,%30,%31,%32,%33,%34,%35,%36,%37,%38,%39,%40,%41,%42,%43,%44,%45,%46,%47,%48,%49,%50,%51,%52,%53,%54,%55,%56,%57,%58,%59,%60,%61,%62,%63}, da, db, p, 1, 1, 1, 0;\n}\n"
    : "=f"(d[0]),"=f"(d[1]),"=f"(d[2]),"=f"(d[3]),"=f"(d[4]),"=f"(d[5]),"=f"(d[6]),"=f"(d[7]),"=f"(d[8]),"=f"(d[9]),"=f"(d[10]),"=f"(d[11]),"=f"(d[12]),"=f"(d[13]),"=f"(d[14]),"=f"(d[15]),"=f"(d[16]),"=f"(d[17]),"=f"(d[18]),"=f"(d[19]),"=f"(d[20]),"=f"(d[21]),"=f"(d[22]),"=f"(d[23]),"=f"(d[24]),"=f"(d[25]),"=f"(d[26]),"=f"(d[27]),"=f"(d[28]),"=f"(d[29]),"=f"(d[30]),"=f"(d[31]),"=f"(d[32]),"=f"(d[33]),"=f"(d[34]),"=f"(d[35]),"=f"(d[36]),"=f"(d[37]),"=f"(d[38]),"=f"(d[39]),"=f"(d[40]),"=f"(d[41]),"=f"(d[42]),"=f"(d[43]),"=f"(d[44]),"=f"(d[45]),"=f"(d[46]),"=f"(d[47]),"=f"(d[48]),"=f"(d[49]),"=f"(d[50]),"=f"(d[51]),"=f"(d[52]),"=f"(d[53]),"=f"(d[54]),"=f"(d[55]),"=f"(d[56]),"=f"(d[57]),"=f"(d[58]),"=f"(d[59]),"=f"(d[60]),"=f"(d[61]),"=f"(d[62]),"=f"(d[63])
    : "r"(al), "r"(bl), "n"(HA), "n"(HB));
}
template<uint32_t HA, uint32_t HB, int NN> __device__ __forceinline__ void wg128_ss_ta_tb(float (&d)[NN], uint32_t al, uint32_t bl) {
  asm volatile("{\n.reg .pred p;\n.reg .b64 da, db;\nsetp.ne.b32 p, 1, 0;\nmov.b64 da, {%64, %66};\nmov.b64 db, {%65, %67};\n"
    "wgmma.mma_async.sync.aligned.m64n128k16.f32.bf16.bf16 {%0,%1,%2,%3,%4,%5,%6,%7,%8,%9,%10,%11,%12,%13,%14,%15,%16,%17,%18,%19,%20,%21,%22,%23,%24,%25,%26,%27,%28,%29,%30,%31,%32,%33,%34,%35,%36,%37,%38,%39,%40,%41,%42,%43,%44,%45,%46,%47,%48,%49,%50,%51,%52,%53,%54,%55,%56,%57,%58,%59,%60,%61,%62,%63}, da, db, p, 1, 1, 1, 1;\n}\n"
    : "+f"(d[0]),"+f"(d[1]),"+f"(d[2]),"+f"(d[3]),"+f"(d[4]),"+f"(d[5]),"+f"(d[6]),"+f"(d[7]),"+f"(d[8]),"+f"(d[9]),"+f"(d[10]),"+f"(d[11]),"+f"(d[12]),"+f"(d[13]),"+f"(d[14]),"+f"(d[15]),"+f"(d[16]),"+f"(d[17]),"+f"(d[18]),"+f"(d[19]),"+f"(d[20]),"+f"(d[21]),"+f"(d[22]),"+f"(d[23]),"+f"(d[24]),"+f"(d[25]),"+f"(d[26]),"+f"(d[27]),"+f"(d[28]),"+f"(d[29]),"+f"(d[30]),"+f"(d[31]),"+f"(d[32]),"+f"(d[33]),"+f"(d[34]),"+f"(d[35]),"+f"(d[36]),"+f"(d[37]),"+f"(d[38]),"+f"(d[39]),"+f"(d[40]),"+f"(d[41]),"+f"(d[42]),"+f"(d[43]),"+f"(d[44]),"+f"(d[45]),"+f"(d[46]),"+f"(d[47]),"+f"(d[48]),"+f"(d[49]),"+f"(d[50]),"+f"(d[51]),"+f"(d[52]),"+f"(d[53]),"+f"(d[54]),"+f"(d[55]),"+f"(d[56]),"+f"(d[57]),"+f"(d[58]),"+f"(d[59]),"+f"(d[60]),"+f"(d[61]),"+f"(d[62]),"+f"(d[63])
    : "r"(al), "r"(bl), "n"(HA), "n"(HB));
}
template<uint32_t HA, uint32_t HB, int NN> __device__ __forceinline__ void wg128_ss_ta_tb_z(float (&d)[NN], uint32_t al, uint32_t bl) {
  asm volatile("{\n.reg .pred p;\n.reg .b64 da, db;\nsetp.ne.b32 p, 0, 0;\nmov.b64 da, {%64, %66};\nmov.b64 db, {%65, %67};\n"
    "wgmma.mma_async.sync.aligned.m64n128k16.f32.bf16.bf16 {%0,%1,%2,%3,%4,%5,%6,%7,%8,%9,%10,%11,%12,%13,%14,%15,%16,%17,%18,%19,%20,%21,%22,%23,%24,%25,%26,%27,%28,%29,%30,%31,%32,%33,%34,%35,%36,%37,%38,%39,%40,%41,%42,%43,%44,%45,%46,%47,%48,%49,%50,%51,%52,%53,%54,%55,%56,%57,%58,%59,%60,%61,%62,%63}, da, db, p, 1, 1, 1, 1;\n}\n"
    : "=f"(d[0]),"=f"(d[1]),"=f"(d[2]),"=f"(d[3]),"=f"(d[4]),"=f"(d[5]),"=f"(d[6]),"=f"(d[7]),"=f"(d[8]),"=f"(d[9]),"=f"(d[10]),"=f"(d[11]),"=f"(d[12]),"=f"(d[13]),"=f"(d[14]),"=f"(d[15]),"=f"(d[16]),"=f"(d[17]),"=f"(d[18]),"=f"(d[19]),"=f"(d[20]),"=f"(d[21]),"=f"(d[22]),"=f"(d[23]),"=f"(d[24]),"=f"(d[25]),"=f"(d[26]),"=f"(d[27]),"=f"(d[28]),"=f"(d[29]),"=f"(d[30]),"=f"(d[31]),"=f"(d[32]),"=f"(d[33]),"=f"(d[34]),"=f"(d[35]),"=f"(d[36]),"=f"(d[37]),"=f"(d[38]),"=f"(d[39]),"=f"(d[40]),"=f"(d[41]),"=f"(d[42]),"=f"(d[43]),"=f"(d[44]),"=f"(d[45]),"=f"(d[46]),"=f"(d[47]),"=f"(d[48]),"=f"(d[49]),"=f"(d[50]),"=f"(d[51]),"=f"(d[52]),"=f"(d[53]),"=f"(d[54]),"=f"(d[55]),"=f"(d[56]),"=f"(d[57]),"=f"(d[58]),"=f"(d[59]),"=f"(d[60]),"=f"(d[61]),"=f"(d[62]),"=f"(d[63])
    : "r"(al), "r"(bl), "n"(HA), "n"(HB));
}
template<uint32_t HB, int NN> __device__ __forceinline__ void wg32_rs(float (&d)[NN], uint32_t a0, uint32_t a1, uint32_t a2, uint32_t a3, uint32_t bl) {
  asm volatile("{\n.reg .pred p;\n.reg .b64 db;\nsetp.ne.b32 p, 1, 0;\nmov.b64 db, {%20, %21};\n"
    "wgmma.mma_async.sync.aligned.m64n32k16.f32.bf16.bf16 {%0,%1,%2,%3,%4,%5,%6,%7,%8,%9,%10,%11,%12,%13,%14,%15}, {%16,%17,%18,%19}, db, p, 1, 1, 0;\n}\n"
    : "+f"(d[0]),"+f"(d[1]),"+f"(d[2]),"+f"(d[3]),"+f"(d[4]),"+f"(d[5]),"+f"(d[6]),"+f"(d[7]),"+f"(d[8]),"+f"(d[9]),"+f"(d[10]),"+f"(d[11]),"+f"(d[12]),"+f"(d[13]),"+f"(d[14]),"+f"(d[15])
    : "r"(a0), "r"(a1), "r"(a2), "r"(a3), "r"(bl), "n"(HB));
}
template<uint32_t HA, uint32_t HB, int NN> __device__ __forceinline__ void wg32_ss(float (&d)[NN], uint32_t al, uint32_t bl) {
  asm volatile("{\n.reg .pred p;\n.reg .b64 da, db;\nsetp.ne.b32 p, 1, 0;\nmov.b64 da, {%16, %18};\nmov.b64 db, {%17, %19};\n"
    "wgmma.mma_async.sync.aligned.m64n32k16.f32.bf16.bf16 {%0,%1,%2,%3,%4,%5,%6,%7,%8,%9,%10,%11,%12,%13,%14,%15}, da, db, p, 1, 1, 0, 0;\n}\n"
    : "+f"(d[0]),"+f"(d[1]),"+f"(d[2]),"+f"(d[3]),"+f"(d[4]),"+f"(d[5]),"+f"(d[6]),"+f"(d[7]),"+f"(d[8]),"+f"(d[9]),"+f"(d[10]),"+f"(d[11]),"+f"(d[12]),"+f"(d[13]),"+f"(d[14]),"+f"(d[15])
    : "r"(al), "r"(bl), "n"(HA), "n"(HB));
}
template<uint32_t HA, uint32_t HB, int NN> __device__ __forceinline__ void wg32_ss_z(float (&d)[NN], uint32_t al, uint32_t bl) {
  asm volatile("{\n.reg .pred p;\n.reg .b64 da, db;\nsetp.ne.b32 p, 0, 0;\nmov.b64 da, {%16, %18};\nmov.b64 db, {%17, %19};\n"
    "wgmma.mma_async.sync.aligned.m64n32k16.f32.bf16.bf16 {%0,%1,%2,%3,%4,%5,%6,%7,%8,%9,%10,%11,%12,%13,%14,%15}, da, db, p, 1, 1, 0, 0;\n}\n"
    : "=f"(d[0]),"=f"(d[1]),"=f"(d[2]),"=f"(d[3]),"=f"(d[4]),"=f"(d[5]),"=f"(d[6]),"=f"(d[7]),"=f"(d[8]),"=f"(d[9]),"=f"(d[10]),"=f"(d[11]),"=f"(d[12]),"=f"(d[13]),"=f"(d[14]),"=f"(d[15])
    : "r"(al), "r"(bl), "n"(HA), "n"(HB));
}
template<uint32_t HA, uint32_t HB, int NN> __device__ __forceinline__ void wg32_ss_ta_tb(float (&d)[NN], uint32_t al, uint32_t bl) {
  asm volatile("{\n.reg .pred p;\n.reg .b64 da, db;\nsetp.ne.b32 p, 1, 0;\nmov.b64 da, {%16, %18};\nmov.b64 db, {%17, %19};\n"
    "wgmma.mma_async.sync.aligned.m64n32k16.f32.bf16.bf16 {%0,%1,%2,%3,%4,%5,%6,%7,%8,%9,%10,%11,%12,%13,%14,%15}, da, db, p, 1, 1, 1, 1;\n}\n"
    : "+f"(d[0]),"+f"(d[1]),"+f"(d[2]),"+f"(d[3]),"+f"(d[4]),"+f"(d[5]),"+f"(d[6]),"+f"(d[7]),"+f"(d[8]),"+f"(d[9]),"+f"(d[10]),"+f"(d[11]),"+f"(d[12]),"+f"(d[13]),"+f"(d[14]),"+f"(d[15])
    : "r"(al), "r"(bl), "n"(HA), "n"(HB));
}
template<uint32_t HA, uint32_t HB, int NN> __device__ __forceinline__ void wg32_ss_ta_tb_z(float (&d)[NN], uint32_t al, uint32_t bl) {
  asm volatile("{\n.reg .pred p;\n.reg .b64 da, db;\nsetp.ne.b32 p, 0, 0;\nmov.b64 da, {%16, %18};\nmov.b64 db, {%17, %19};\n"
    "wgmma.mma_async.sync.aligned.m64n32k16.f32.bf16.bf16 {%0,%1,%2,%3,%4,%5,%6,%7,%8,%9,%10,%11,%12,%13,%14,%15}, da, db, p, 1, 1, 1, 1;\n}\n"
    : "=f"(d[0]),"=f"(d[1]),"=f"(d[2]),"=f"(d[3]),"=f"(d[4]),"=f"(d[5]),"=f"(d[6]),"=f"(d[7]),"=f"(d[8]),"=f"(d[9]),"=f"(d[10]),"=f"(d[11]),"=f"(d[12]),"=f"(d[13]),"=f"(d[14]),"=f"(d[15])
    : "r"(al), "r"(bl), "n"(HA), "n"(HB));
}
template<uint32_t HA, uint32_t HB, int NN> __device__ __forceinline__ void wg64_ss_ta_tb(float (&d)[NN], uint32_t al, uint32_t bl) {
  asm volatile("{\n.reg .pred p;\n.reg .b64 da, db;\nsetp.ne.b32 p, 1, 0;\nmov.b64 da, {%32, %34};\nmov.b64 db, {%33, %35};\n"
    "wgmma.mma_async.sync.aligned.m64n64k16.f32.bf16.bf16 {%0,%1,%2,%3,%4,%5,%6,%7,%8,%9,%10,%11,%12,%13,%14,%15,%16,%17,%18,%19,%20,%21,%22,%23,%24,%25,%26,%27,%28,%29,%30,%31}, da, db, p, 1, 1, 1, 1;\n}\n"
    : "+f"(d[0]),"+f"(d[1]),"+f"(d[2]),"+f"(d[3]),"+f"(d[4]),"+f"(d[5]),"+f"(d[6]),"+f"(d[7]),"+f"(d[8]),"+f"(d[9]),"+f"(d[10]),"+f"(d[11]),"+f"(d[12]),"+f"(d[13]),"+f"(d[14]),"+f"(d[15]),"+f"(d[16]),"+f"(d[17]),"+f"(d[18]),"+f"(d[19]),"+f"(d[20]),"+f"(d[21]),"+f"(d[22]),"+f"(d[23]),"+f"(d[24]),"+f"(d[25]),"+f"(d[26]),"+f"(d[27]),"+f"(d[28]),"+f"(d[29]),"+f"(d[30]),"+f"(d[31])
    : "r"(al), "r"(bl), "n"(HA), "n"(HB));
}
template<uint32_t HA, uint32_t HB, int NN> __device__ __forceinline__ void wg64_ss_ta_tb_z(float (&d)[NN], uint32_t al, uint32_t bl) {
  asm volatile("{\n.reg .pred p;\n.reg .b64 da, db;\nsetp.ne.b32 p, 0, 0;\nmov.b64 da, {%32, %34};\nmov.b64 db, {%33, %35};\n"
    "wgmma.mma_async.sync.aligned.m64n64k16.f32.bf16.bf16 {%0,%1,%2,%3,%4,%5,%6,%7,%8,%9,%10,%11,%12,%13,%14,%15,%16,%17,%18,%19,%20,%21,%22,%23,%24,%25,%26,%27,%28,%29,%30,%31}, da, db, p, 1, 1, 1, 1;\n}\n"
    : "=f"(d[0]),"=f"(d[1]),"=f"(d[2]),"=f"(d[3]),"=f"(d[4]),"=f"(d[5]),"=f"(d[6]),"=f"(d[7]),"=f"(d[8]),"=f"(d[9]),"=f"(d[10]),"=f"(d[11]),"=f"(d[12]),"=f"(d[13]),"=f"(d[14]),"=f"(d[15]),"=f"(d[16]),"=f"(d[17]),"=f"(d[18]),"=f"(d[19]),"=f"(d[20]),"=f"(d[21]),"=f"(d[22]),"=f"(d[23]),"=f"(d[24]),"=f"(d[25]),"=f"(d[26]),"=f"(d[27]),"=f"(d[28]),"=f"(d[29]),"=f"(d[30]),"=f"(d[31])
    : "r"(al), "r"(bl), "n"(HA), "n"(HB));
}

__device__ __forceinline__ void mbar_init(uint32_t a, uint32_t c) { asm volatile("mbarrier.init.shared::cta.b64 [%0], %1;" ::"r"(a), "r"(c) : "memory"); }
__device__ __forceinline__ void mbar_expect(uint32_t a, uint32_t b) { asm volatile("mbarrier.arrive.expect_tx.shared::cta.b64 _, [%0], %1;" ::"r"(a), "r"(b) : "memory"); }
__device__ __forceinline__ void mbar_arrive(uint32_t a) { asm volatile("mbarrier.arrive.shared::cta.b64 _, [%0];" ::"r"(a) : "memory"); }
__device__ __forceinline__ void mbar_wait(uint32_t a) {
  asm volatile("{\n.reg .pred p;\n.reg .u32 n;\n"
               "mbarrier.try_wait.parity.shared::cta.b64 p, [%0], 0, 20000;\n@p bra LD;\nmov.u32 n, 0;\nLW:\n"
               "mbarrier.try_wait.parity.shared::cta.b64 p, [%0], 0, 20000;\n@p bra LD;\n"
               "add.u32 n, n, 1;\nsetp.lt.u32 p, n, 0x40000;\n@p bra LW;\ntrap;\nLD:\n}\n" ::"r"(a) : "memory");
}
__device__ __forceinline__ void mbar_wait_c(uint32_t a) {
  asm volatile("{\n.reg .pred p;\nLW:\nmbarrier.try_wait.parity.shared::cta.b64 p, [%0], 0;\n@!p bra LW;\n}\n" ::"r"(a) : "memory");
}
__device__ __forceinline__ bool elect() {
  uint32_t r;
  asm volatile("{\n.reg .pred p;\nelect.sync _|p, 0xffffffff;\nselp.u32 %0, 1, 0, p;\n}\n" : "=r"(r));
  return r;
}
__device__ __forceinline__ void warp_arrive(uint32_t a) { __syncwarp(); if ((threadIdx.x & 31) == 0) mbar_arrive(a); }
__device__ __forceinline__ void wg_bar(int wg) { asm volatile("bar.sync %0, 128;" ::"r"(1 + wg) : "memory"); }
__device__ __forceinline__ void tma2d(uint32_t dst, const CUtensorMap* m, int c0, int c1, uint32_t bar) {
  asm volatile("cp.async.bulk.tensor.2d.shared::cluster.global.mbarrier::complete_tx::bytes [%0], [%1, {%3, %4}], [%2];"
               ::"r"(dst), "l"(m), "r"(bar), "r"(c0), "r"(c1) : "memory");
}
__device__ __forceinline__ void bulk(uint32_t dst, const void* src, uint32_t bytes, uint32_t bar) {
  asm volatile("cp.async.bulk.shared::cluster.global.mbarrier::complete_tx::bytes [%0], [%1], %2, [%3];"
               ::"r"(dst), "l"(src), "r"(bytes), "r"(bar) : "memory");
}
__device__ __forceinline__ void async_fence() { asm volatile("fence.proxy.async.shared::cta;" ::: "memory"); }
__device__ __forceinline__ void async_fence_global() { asm volatile("fence.proxy.async.global;" ::: "memory"); }
__device__ __forceinline__ void bulk_st(void* dst, uint32_t src, uint32_t bytes) {
  asm volatile("cp.async.bulk.global.shared::cta.bulk_group [%0], [%1], %2;" ::"l"(dst), "r"(src), "r"(bytes) : "memory");
}
__device__ __forceinline__ void bulk_st_wait() { asm volatile("cp.async.bulk.commit_group;\ncp.async.bulk.wait_group 0;" ::: "memory"); }
__device__ __forceinline__ void signal(Scratch* G, int c) { asm volatile("red.release.gpu.global.add.u32 [%0], 1;" ::"l"(&G->cnt[c * 32]) : "memory"); }
__device__ __forceinline__ void bump(unsigned* p) { asm volatile("red.relaxed.gpu.global.add.u32 [%0], 1;" ::"l"(p) : "memory"); }
__device__ __forceinline__ unsigned ld_epoch(Scratch* G, int b) { unsigned v; asm volatile("ld.relaxed.gpu.global.u32 %0, [%1];" : "=r"(v) : "l"(&G->epoch[b]) : "memory"); return v + 1; }
template <int SLEEP, bool TWO = false> __device__ __forceinline__ void poll(Scratch* G, unsigned target, int c0, int c1 = 0) {
  const unsigned *p0 = &G->cnt[c0 * 32], *p1 = &G->cnt[c1 * 32];
  for (int n = 0;; n++) {
    unsigned a, b;
    if (TWO) asm volatile("ld.relaxed.gpu.global.u32 %0, [%2];\nld.relaxed.gpu.global.u32 %1, [%3];" : "=r"(a), "=r"(b) : "l"(p0), "l"(p1) : "memory");
    else { asm volatile("ld.relaxed.gpu.global.u32 %0, [%1];" : "=r"(a) : "l"(p0) : "memory"); b = a; }
    if ((int)((a - target) | (b - target)) >= 0) break;
    if (n > (1 << 22)) __trap();
    if (SLEEP) __nanosleep(SLEEP);
  }
  asm volatile("fence.acquire.gpu;" ::: "memory");
  async_fence_global();
}
__device__ __forceinline__ float ex2(float x) { float y; asm("ex2.approx.ftz.f32 %0, %1;" : "=f"(y) : "f"(x)); return y; }
__device__ __forceinline__ float rcp(float x) { float y; asm("rcp.approx.ftz.f32 %0, %1;" : "=f"(y) : "f"(x)); return y; }
__device__ __forceinline__ uint32_t pack(float lo, float hi) { uint32_t y; asm("cvt.rn.bf16x2.f32 %0, %1, %2;" : "=r"(y) : "f"(hi), "f"(lo)); return y; }
__device__ __forceinline__ void sts128(uint32_t a, uint32_t x, uint32_t y, uint32_t z, uint32_t w) {
  asm volatile("st.shared.v4.u32 [%0], {%1,%2,%3,%4};" ::"r"(a), "r"(x), "r"(y), "r"(z), "r"(w) : "memory");
}
__device__ __forceinline__ uint32_t lds(uint32_t a) { uint32_t v; asm volatile("ld.shared.u32 %0, [%1];" : "=r"(v) : "r"(a) : "memory"); return v; }
__device__ __forceinline__ uint32_t hsq(uint32_t v, uint32_t a) { uint32_t y; asm("fma.rn.bf16x2 %0, %1, %1, %2;" : "=r"(y) : "r"(v), "r"(a)); return y; }
__device__ __forceinline__ uint32_t hadd(uint32_t a, uint32_t b) { uint32_t y; asm("add.rn.bf16x2 %0, %1, %2;" : "=r"(y) : "r"(a), "r"(b)); return y; }
__device__ __forceinline__ uint32_t exp2_pair(float t0, float t1) {
  const uint32_t w = __byte_perm(__float_as_uint(t0), __float_as_uint(t1), 0x6521), m = w | 0x3F803F80u;
  return hsq(m, 0x40014001u) + w - m;
}
__device__ __forceinline__ uint32_t phi2(float t0, float t1) {
  uint32_t r;
  asm("cvt.rn.relu.bf16x2.f32 %0, %1, %2;" : "=r"(r) : "f"(t1), "f"(t0));
  return hadd(r, pack(__saturatef(ex2(t0 * 1.4426950408889634f) + 1e-6f), __saturatef(ex2(t1 * 1.4426950408889634f) + 1e-6f)));
}

constexpr uint32_t H_SW = (1024 >> 4) | (1u << 30), L_X = 1u << 16, L_W = (8192u >> 4) << 16;
constexpr uint32_t H_T = (2048 >> 4) | (2u << 30), L_T = (512u >> 4) << 16;
constexpr uint32_t H_KV = 128 >> 4, L_KV = (512u >> 4) << 16;

__device__ __forceinline__ void stage_o(const float* o, float eps, uint32_t a, int src, uint32_t free_bar) {
  const float r0 = __shfl_sync(~0u, rcp(o[12] + eps), src), r1 = __shfl_sync(~0u, rcp(o[14] + eps), src);
  uint32_t v[8];
#pragma unroll
  for (int i = 0; i < 8; i++) v[i] = pack(o[2 * i] * ((i & 1) ? r1 : r0), o[2 * i + 1] * ((i & 1) ? r1 : r0));
  if (free_bar) { pin<8>(v); mbar_wait_c(free_bar); }
#pragma unroll
  for (int c = 0; c < 2; c++)
    asm volatile("stmatrix.sync.aligned.m8n8.x4.trans.shared.b16 [%0], {%1,%2,%3,%4};"
                 ::"r"(a + c * 4096), "r"(v[4 * c]), "r"(v[4 * c + 1]), "r"(v[4 * c + 2]), "r"(v[4 * c + 3]) : "memory");
}
__device__ __forceinline__ void flush_o(uint8_t* dst, uint32_t base, int odd) {
  async_fence();
#pragma unroll
  for (int c = 0; c < 3; c++) bulk_st(dst + odd * 4096 + c * 1024, base + c * 2048, 1024);
  bulk_st(dst + 3072 + odd * 512, base + 6144 + odd * 512, 512);
}

__device__ __forceinline__ void mma16816(float* d, uint32_t a0, uint32_t a1, uint32_t a2, uint32_t a3, uint32_t b0, uint32_t b1) {
  asm volatile("mma.sync.aligned.m16n8k16.row.col.f32.bf16.bf16.f32 {%0,%1,%2,%3}, {%4,%5,%6,%7}, {%8,%9}, {%0,%1,%2,%3};"
               : "+f"(d[0]), "+f"(d[1]), "+f"(d[2]), "+f"(d[3]) : "r"(a0), "r"(a1), "r"(a2), "r"(a3), "r"(b0), "r"(b1));
}
__device__ __forceinline__ uint32_t trans(uint32_t v) { uint32_t y; asm volatile("movmatrix.sync.aligned.m8n8.trans.b16 %0, %1;" : "=r"(y) : "r"(v)); return y; }
__device__ __forceinline__ void attn_safe(float* o, const uint8_t* qp, int qg, const uint8_t* kv, bool odd, int lane) {
  auto blk = [&](const uint8_t* p, int kg, int c) {
    return __ldcg((const uint32_t*)(p + c * 2048 + (kg >> 2) * 512 + (lane >> 2) * 64 + ((kg & 3) ^ (lane >> 3)) * 16 + (lane & 3) * 4));
  };
  uint32_t q[8];
#pragma unroll
  for (int i = 0; i < 8; i++) q[i] = trans(blk(qp, qg + (i & 1), i >> 1));
  if (((lane & 2) != 0) != odd) q[6] = q[7] = 0;
  float m0 = -INFINITY, m1 = -INFINITY;
#pragma unroll
  for (int i = 0; i < 16; i++) o[i] = 0.f;
#pragma unroll 1
  for (int it = 0; it < 128; it++) {
    const uint8_t* k = kv + (it >> 3) * M_STRIDE;
    uint32_t kb[8], vb[8];
#pragma unroll
    for (int i = 0; i < 8; i++) { kb[i] = trans(blk(k, (it & 7) * 2 + (i >> 2), i & 3)); vb[i] = blk(k + SEC_STRIDE, (it & 7) * 2 + (i >> 2), i & 3); }
    float s[8];
#pragma unroll
    for (int b = 0; b < 2; b++) {
      s[4 * b] = s[4 * b + 1] = s[4 * b + 2] = s[4 * b + 3] = 0.f;
      mma16816(s + 4 * b, q[0], q[1], q[2], q[3], kb[4 * b], kb[4 * b + 1]);
      mma16816(s + 4 * b, q[4], q[5], q[6], q[7], kb[4 * b + 2], kb[4 * b + 3]);
    }
    float n0 = fmaxf(fmaxf(s[0], s[1]), fmaxf(s[4], s[5])), n1 = fmaxf(fmaxf(s[2], s[3]), fmaxf(s[6], s[7]));
    n0 = fmaxf(n0, __shfl_xor_sync(~0u, n0, 1)); n1 = fmaxf(n1, __shfl_xor_sync(~0u, n1, 1));
    n0 = fmaxf(n0, __shfl_xor_sync(~0u, n0, 2)); n1 = fmaxf(n1, __shfl_xor_sync(~0u, n1, 2));
    n0 = fmaxf(n0, m0); n1 = fmaxf(n1, m1);
    const float a0 = ex2(m0 - n0), a1 = ex2(m1 - n1);
    m0 = n0; m1 = n1;
    const uint32_t p0 = pack(ex2(s[0] - m0), ex2(s[1] - m0)), p1 = pack(ex2(s[2] - m1), ex2(s[3] - m1));
    const uint32_t p2 = pack(ex2(s[4] - m0), ex2(s[5] - m0)), p3 = pack(ex2(s[6] - m1), ex2(s[7] - m1));
#pragma unroll
    for (int c = 0; c < 4; c++) {
      o[4 * c] *= a0; o[4 * c + 1] *= a0; o[4 * c + 2] *= a1; o[4 * c + 3] *= a1;
      mma16816(o + 4 * c, p0, p1, p2, p3, vb[c], vb[4 + c]);
    }
  }
}

__global__ void __launch_bounds__(NTHREADS, 1)
fused_kernel(Scratch* __restrict__ G, uint8_t* __restrict__ out, const uint8_t* xa, const uint8_t* wa, const __grid_constant__ Params P) {
  extern __shared__ __align__(1024) uint8_t smem_raw[];
  if ((threadIdx.x >> 5) == 17 && blockIdx.x < 128) {
    const unsigned l = threadIdx.x & 31, b = blockIdx.x;
    const uint8_t* p = l < 16 ? xa + (b * 16 + l) * 896 : wa + (b >> 1) * 2688 + ((b & 1) * 7 + l - 16) * 128;
    if (l < 23) {
      asm volatile("prefetch.global.L2 [%0];" ::"l"(p));
      asm volatile("prefetch.global.L2 [%0];" ::"l"(p + (l < 16 ? 128 : 64 * 2688)));
    }
  }
  uint8_t* const sm = smem_raw - SB;
  const int bid = blockIdx.x, tid = threadIdx.x, lane = tid & 31;
  const int warp = __shfl_sync(~0u, tid >> 5, 0);
  const bool spare = bid >= 130 || bid == 112 || bid == 113;
  const int L = spare ? (bid >= 130 ? bid - 128 : bid - 112) : (bid < 112 ? bid : bid - 2);
  const int h = L >> 3, qb = L & 7, hb = h & 1, bb = (L >> 4) & 1;
  const int gm = 4 * (L >> 5) + (qb < 6 ? 2 * hb + (qb >= 3) : 2 * bb + hb);
  const int gs = qb < 6 ? 4 * bb + qb - (qb >= 3 ? 3 : 0) : qb == 6 ? 3 : 7;
  const bool qcta = qb == 7 && !spare, reg = !spare && !qcta;
  const int m64 = (h >> 1) * 4 + hb;
  const int np = spare ? 8 : 5;
  auto p_br = [&](int p) { return (!reg || p >= 3) ? 1 : 0; };
  auto p_m = [&](int p) { return spare ? 4 * L + (p >> 1) : gm; };
  auto p_box = [&](int p) { return spare ? 5 + (p & 1) : qcta ? p : gs + 7 * (p >= 3 ? p - 2 : p); };
  auto init_group = [&](int g) {
    if (elect()) {
      const uint32_t cnt = g < 10 ? 1 : g < 18 ? 4 : 16;
#pragma unroll
      for (int i = 0; i < 8; i++) mbar_init(BAR(0) + g * 64 + i * 8, cnt);
      if (g == 19) {
#pragma unroll
        for (int i = 160; i < 166; i++) mbar_init(BAR(i), i < B_WOA2 ? 16 : 1);
      }
    }
    __syncwarp();
    asm volatile("fence.mbarrier_init.release.cluster;\nbar.sync 0, 608;" ::: "memory");
  };
  auto load_first = [&](int kc) {
    const uint32_t fb = BAR(B_F) + 8 * kc;
    mbar_expect(fb, 24576);
    tma2d(S_X + kc * 16384, &P.x[p_br(0)], kc * 64, p_m(0) * 128, fb);
    tma2d(S_W0 + kc * 8192, &P.w[p_br(0)], p_box(0) * 64, kc * 64, fb);
  };
  auto load_second = [&](int kc) {
    const uint32_t fb = BAR(B_F + 7) + 8 * kc;
    mbar_expect(fb, 8192);
    tma2d(S_W1 + kc * 8192, &P.w[p_br(1)], p_box(1) * 64, kc * 64, fb);
  };

  if (warp == 16) {
    if (elect()) {
#pragma unroll
      for (int i = 0; i < 16; i++) mbar_init(BAR(i), 1);
    }
    __syncwarp();
    asm volatile("fence.mbarrier_init.release.cluster;\nbar.arrive 0, 608;" ::: "memory");
    if (elect()) {
      load_first(0); load_first(1); load_second(0); load_second(1);
      if (reg) {
#pragma unroll
        for (int kc = 2; kc < 7; kc++) load_first(kc);
      }
    }
    __syncwarp();
  }
  if (warp >= 16) {
    asm volatile("setmaxnreg.dec.sync.aligned.u32 32;");
    if (warp != 16) {
      if ((uint32_t)__cvta_generic_to_shared(smem_raw) != SB) __trap();
      if (warp == 17) asm volatile("bar.sync 6, 64;" ::: "memory");
      else init_group(warp);
      if (warp == 18) asm volatile("bar.arrive 5, 64;" ::: "memory");
      if (warp == 19) asm volatile("bar.arrive 6, 64;" ::: "memory");
    }
    auto load_oa = [&](int w, unsigned ep) {
#pragma unroll
      for (int kc = 0; kc < 7; kc++) mbar_expect(BAR(B_OF + 7 + 7 * w + kc), 8192);
      mbar_wait(BAR(B_OF));
      mbar_wait(BAR(B_KE + 15));
      poll<0>(G, ep * 16, C_OA + m64 + 2 * w);
      if (w) mbar_wait(BAR(B_AISS));
#pragma unroll
      for (int kc = 0; kc < 7; kc++) {
        if (!w && kc == 5) mbar_arrive(BAR(B_AISS));
        mbar_wait(kc ? BAR(B_OE + 7 * w + kc - 1) : w ? BAR(B_QFREE) : BAR(B_KE + 16));
        bulk(oa_slot(kc, w), G->o[0] + (m64 + 2 * w) * 57344 + kc * 8192, 8192, BAR(B_OF + 7 + 7 * w + kc));
      }
    };
    auto reduce_kv = [&](int i0, int i1) {
      mbar_wait(BAR(B_PART));
#pragma unroll 1
      for (int it = i0; it < i1; it++) {
        float4 a = *(const float4*)(sm + S_PKV + it * 512 + lane * 16);
#pragma unroll
        for (int p = 1; p < 8; p++) {
          float4 v = *(const float4*)(sm + S_PKV + p * 4096 + it * 512 + lane * 16);
          a.x += v.x; a.y += v.y; a.z += v.z; a.w += v.w;
        }
        *(uint2*)(sm + S_KVM + it * 256 + lane * 8) = make_uint2(pack(a.x, a.y), pack(a.z, a.w));
      }
      async_fence();
      warp_arrive(BAR(B_OBGO));
    };
    if (warp == 16) {
      asm volatile("bar.sync 5, 64;" ::: "memory");
      if (elect()) {
#pragma unroll 1
        for (int kc = 2; kc < 7; kc++) {
          if (!reg) {
            if (kc >= 3) mbar_wait(BAR(B_F - 3) + 8 * kc);
            load_first(kc);
          }
          load_second(kc);
        }
        const unsigned ep = ld_epoch(G, bid);
#pragma unroll 1
        for (int q = 0; q < (spare ? 6 : 1); q++) {
          const bool xn = spare && (q & 1), xnn = spare && !(q & 1);
          const uint32_t wdst = (q & 1) ? S_W1 : S_W0;
          const int xrow = p_m(q + 1) * 128, wcol = p_box(q + 2) * 64;
          const CUtensorMap* wm = &P.w[p_br(q + 2)];
#pragma unroll 1
          for (int kc = 0; kc < 7; kc++) {
            const uint32_t b = BAR(0) + 8 * (q * 7 + kc);
            mbar_wait(b + 8 * B_E);
            if (xn) tma2d(S_X + kc * 16384, &P.x[1], kc * 64, xrow, b + 8 * (B_F + 7));
            mbar_expect(b + 8 * (B_F + 14), xnn ? 24576 : 8192);
            tma2d(wdst + kc * 8192, wm, wcol, kc * 64, b + 8 * (B_F + 14));
            if (!spare) { mbar_expect(b + 8 * (B_F + 21), reg ? 24576 : 8192); mbar_expect(b + 8 * (B_F + 28), 8192); }
            if (qcta) {
              mbar_wait(b + 8 * (B_E + 7));
              const bool w3 = kc == 0 || kc >= 5;
              const int k2 = kc == 0 ? 0 : w3 ? kc - 4 : kc - 1;
              tma2d(S_W1 + kc * 8192, wm, w3 ? 192 : 256, k2 * 64, BAR(B_F) + 8 * ((w3 ? 21 : 28) + k2));
            }
          }
        }
        if (!spare) {
          const int c3 = p_box(3) * 64, c4 = p_box(4) * 64;
          auto ldx = [&](int kc) { tma2d(slot(T_XB, kc), &P.x[1], kc * 64, gm * 128, BAR(B_F + 21 + kc)); };
          auto ld3 = [&](int kc) { tma2d(slot(T_W3, kc), &P.w[1], c3, kc * 64, BAR(B_F + 21 + kc)); };
          auto ld4 = [&](int kc) { tma2d(slot(T_W4, kc), &P.w[1], c4, kc * 64, BAR(B_F + 28 + kc)); };
          auto ld4q = [&](int kc) { tma2d(slot(T_W4Q, kc), &P.w[1], c4, kc * 64, BAR(B_F + 28 + kc)); };
          if (reg) {
            mbar_wait(BAR(B_E + 7)); ld3(0);
            mbar_wait(BAR(B_E + 9)); ldx(0);
            mbar_wait(BAR(B_E + 11)); ldx(1);
            mbar_wait(BAR(B_E + 12)); ld3(1);
            mbar_wait(BAR(B_E + 13)); ld3(2);
          }
#pragma unroll
          for (int kc = 0; kc < 7; kc++) {
            mbar_wait(BAR(B_E + 14 + kc));
            if (reg && kc < 5) ldx(kc + 2);
            if (kc < 4) ld3(kc + 3);
            else if (!reg) ld4q(kc);
            else if (kc == 4) ld4(0);
            else {
              if (kc == 6) mbar_wait(BAR(B_ASIG));
              ld4(3 * kc - 14); ld4(3 * kc - 13); ld4(3 * kc - 12);
            }
          }
          const uint8_t* src = G->qkv[0] + h * 8192;
          mbar_expect(BAR(B_QF), 16384);
          mbar_expect(BAR(B_QF + 1), 8192);
          mbar_expect(BAR(B_KF), 16384);
          mbar_wait(BAR(B_E + 21 + 6));
          poll<0, true>(G, ep * 16, C_A + (28 * h >> 6), C_A + ((28 * h + 27) >> 6));
          bulk(S_Q, src + (2 * qb) * M_STRIDE, 8192, BAR(B_QF));
          bulk(S_R0, src + SEC_STRIDE, 8192, BAR(B_QF));
          bulk(S_R0 + 8192, src + 2 * SEC_STRIDE, 8192, BAR(B_KF));
          bulk(S_R1, src + M_STRIDE + SEC_STRIDE, 8192, BAR(B_KF));
          bulk(S_Q + 8192, src + (2 * qb + 1) * M_STRIDE, 8192, BAR(B_QF + 1));
#pragma unroll 1
          for (int t = 1; t < 16; t++) {
            mbar_wait(t >= 3 ? BAR(B_KE - 3) + 8 * t : reg ? BAR(B_E + 27) + 8 * t : BAR(B_E + 27) + 16 * t);
            const uint32_t vdst = ((t & 2) ? S_R2 : S_R0) + (t & 1) * 16384 + 8192, fb = BAR(B_KF) + 8 * t;
            const uint32_t kdst = (((t + 1) & 2) ? S_R2 : S_R0) + ((t + 1) & 1) * 16384;
            mbar_expect(fb, t < 15 ? 16384 : 8192);
            bulk(vdst, src + t * M_STRIDE + 2 * SEC_STRIDE, 8192, fb);
            if (t < 15) bulk(kdst, src + (t + 1) * M_STRIDE + SEC_STRIDE, 8192, fb);
            if (t >= 9 && reg) {
              if (t == 9) { mbar_wait(BAR(B_STGF)); mbar_expect(BAR(B_WOB), 57344); }
              tma2d(S_WOB + (t - 9) * 8192, &P.wo[1], qb * 64, (t - 9) * 64, BAR(B_WOB));
            }
          }
          if (reg) {
            poll<50>(G, ep * 16, C_OB + (h >> 1));
#pragma unroll
            for (int i = 0; i < 7; i++) {
              const int kc = i < 2 ? i : i == 2 ? 5 : i < 6 ? i - 1 : 6;
              if (kc >= 2 && kc < 5) mbar_wait(BAR(B_KE + 11 + kc));
              if (kc == 5) mbar_wait(BAR(B_SOB));
              mbar_expect(BAR(B_OF + kc), 16384);
              bulk(ob_slot(kc, 0), G->o[1] + m64 * 57344 + kc * 8192, 8192, BAR(B_OF + kc));
              bulk(ob_slot(kc, 1), G->o[1] + (m64 + 2) * 57344 + kc * 8192, 8192, BAR(B_OF + kc));
            }
            mbar_expect(BAR(B_WOA2), 24576);
            mbar_wait(BAR(B_OGO));
#pragma unroll
            for (int i = 0; i < 3; i++) {
              mbar_wait(BAR(B_OE + i)); mbar_wait(BAR(B_OE + 7 + i));
              tma2d(woa_slot(4 + i), &P.wo[0], qb * 64, (4 + i) * 64, BAR(B_WOA2));
            }
          }
        }
      }
    } else if (spare) {
      if (warp == 19 && elect()) {
#pragma unroll 1
        for (int j = 0; j < 4; j++) {
          mbar_wait(BAR(B_SG) + 16 * j); mbar_wait(BAR(B_SG + 1) + 16 * j);
          signal(G, C_BQ + 2 * L + (j >> 1));
        }
      }
    } else if (warp == 17) {
      const unsigned ep = ld_epoch(G, bid);
      const uint8_t* src = G->qkv[1] + h * 8192 + 2 * qb * M_STRIDE;
      if (elect()) {
        mbar_wait(BAR(B_E + 34));
        poll<100>(G, ep * 14, C_BK + qb);
        mbar_expect(BAR(B_PKV), 32768);
#pragma unroll
        for (int i = 0; i < 4; i++) bulk(S_PKV + i * 8192, src + (i >> 1) * M_STRIDE + (1 + (i & 1)) * SEC_STRIDE, 8192, BAR(B_PKV));
        mbar_wait(BAR(B_SKV));
        poll<100>(G, ep * 8, C_KV + h);
        mbar_expect(BAR(B_PART), 32768);
        bulk(S_PKV, G->part + h * 8192, 32768, BAR(B_PART));
      }
      __syncwarp();
      reduce_kv(0, 3);
      if (elect()) {
        poll<100>(G, ep * 4, C_BQ + qb);
        mbar_expect(BAR(B_OBGO), 16384);
        bulk(S_PQ, src, 8192, BAR(B_OBGO));
        bulk(S_PQ + 8192, src + M_STRIDE, 8192, BAR(B_OBGO));
        if (reg) load_oa(0, ep);
      }
    } else if (warp == 18) {
      const unsigned ep = ld_epoch(G, bid);
      mbar_wait(BAR(B_STGF));
      const uint2* np4 = (lane < 16 ? G->nrm[1][lane] : G->nrm[0][2 * qb + (lane & 1)]) + 4 * h;
      uint4 v0, v1;
      for (int n = 0;; n++) {
        asm volatile("ld.relaxed.gpu.global.v4.u32 {%0,%1,%2,%3}, [%4];" : "=r"(v0.x), "=r"(v0.y), "=r"(v0.z), "=r"(v0.w) : "l"(np4) : "memory");
        asm volatile("ld.relaxed.gpu.global.v4.u32 {%0,%1,%2,%3}, [%4];" : "=r"(v1.x), "=r"(v1.y), "=r"(v1.z), "=r"(v1.w) : "l"(np4 + 2) : "memory");
        if (__all_sync(~0u, v0.y == ep && v0.w == ep && v1.y == ep && v1.w == ep)) break;
        if (n > (1 << 22)) __trap();
        __nanosleep(200);
      }
      const uint32_t n = __float_as_uint((__uint_as_float(v0.x) + __uint_as_float(v0.z)) + (__uint_as_float(v1.x) + __uint_as_float(v1.z))) & 0x7FFFFFFFu;
      const uint32_t kmax = __reduce_max_sync(~0u, lane < 16 ? n : 0u), qmax = __reduce_max_sync(~0u, lane < 16 ? 0u : n);
      if (lane == 0) {
        *(volatile uint32_t*)(sm + S_MISC) = (__uint_as_float(qmax) * __uint_as_float(kmax) <= GUARD) ? 0u : 1u;
        *(volatile uint32_t*)(sm + S_MISC + 4) = 0;
      }
      reduce_kv(3, 6);
      if (reg && elect()) load_oa(1, ep);
    } else {
      if (elect()) {
        if (reg) mbar_wait(BAR(B_PAD));
        mbar_wait(BAR(B_SG)); mbar_wait(BAR(B_SG + 1)); mbar_wait(BAR(B_SG + 2));
        if (reg) { signal(G, C_A + gs); mbar_arrive(BAR(B_ASIG)); }
        mbar_wait(BAR(B_QF + 1)); mbar_wait(BAR(B_KF + 2));
#pragma unroll 1
        for (int i = 0; i < 2; i++) {
          const int j = reg ? gs : 3 + i, n1 = 7 - j, is = j > 3 ? 10 - j : 3 - j;
          uint8_t* dst = G->qkv[1] + gm * M_STRIDE + (reg ? 1 + i : 0) * SEC_STRIDE + 9 * j * 2048;
          const uint32_t src = S_STG + i * 20480;
          mbar_wait(BAR(B_SG + 3) + 8 * i);
          async_fence();
          bulk_st(dst, src, n1 * 2048);
          bulk_st(dst + (n1 + 1) * 2048, src + n1 * 2048, (8 - n1) * 2048);
          bulk_st(dst + (is + (is >= n1) + 4) * 2048, src + 16384, 2048);
          if (j == 3) bulk_st(dst + 12 * 2048, src + 18432, 2048);
        }
        bulk_st_wait();
        signal(G, (reg ? C_BK : C_BQ) + (gm >> 1));
        mbar_arrive(BAR(B_STGF));
      }
      __syncwarp();
      {
        uint8_t* pz = G->o[0] + qb * 4 * 57344 + h * 3584 + lane * 16;
#pragma unroll 1
        for (int i = 0; i < 4; i++) {
          mbar_wait(BAR(B_KF + 4) + 8 * (i >> 1));
#pragma unroll
          for (int c = 0; c < 7; c++) *(uint4*)(pz + i * 57344 + c * 512) = make_uint4(~0u, ~0u, ~0u, ~0u);
        }
      }
      __syncwarp();
      if (elect()) { mbar_wait(BAR(B_SKV)); signal(G, C_KV + h); async_fence_global(); }
      __syncwarp();
      reduce_kv(6, 8);
      if (elect()) {
        uint8_t* od = G->o[1] + qb * 4 * 57344 + 7 * (h >> 1) * 1024;
        mbar_wait(BAR(B_SOB));
#pragma unroll 1
        for (int i = 0; i < 4; i++) flush_o(od + i * 57344, S_PKV + (i >> 1) * 8192 + (i & 1) * 1024, hb);
        bulk_st_wait();
        signal(G, C_OB + qb);
        if (reg) {
          mbar_expect(BAR(B_WOA), 32768);
          mbar_wait(BAR(B_KF + T_OB + 4));
#pragma unroll 1
          for (int i = 0; i < 4; i++) tma2d(S_WOA + i * 8192, &P.wo[0], qb * 64, i * 64, BAR(B_WOA));
#pragma unroll 1
          for (int i = 4; i < 7; i++)
            asm volatile("cp.async.bulk.prefetch.tensor.2d.L2.global [%0, {%1, %2}];" ::"l"(&P.wo[0]), "r"(qb * 64), "r"(i * 64) : "memory");
        }
        mbar_wait(BAR(B_DONE));
        bump(&G->epoch[bid]);
      }
    }
  } else {
    const int wg = warp >> 2, ww = warp & 3, pair = wg >> 1, w = wg & 1;
    init_group(warp ? warp + 1 : 17);
    const bool l0 = lane == 0;
    {
      const int g = lane >> 2, j4 = lane & 3;
      if (reg && wg == 2) {
        const int t = tid & 127, r = (t >> 2) & 3, hd = t >> 6, kg = ((t >> 2) & 12) + ((t & 3) ^ ((r >> 1) + (hd ? 0 : 2)));
        uint8_t* pp = G->qkv[0] + gm * M_STRIDE + (8 * (gs > 3 ? gs + 1 : gs) + 3 + 4 * hd) * 2048 + (kg >> 2) * 512 + (hd ? 0 : 256) + (t & 15) * 16;
        const uint32_t vq = r == 3 ? 0u : 0x3F803F80u, vv = r ? 0u : 0x3F803F80u;
        const uint32_t ve = r == 0 ? 0x43A043A0u : r == 1 ? 0x3FB43FB4u : r == 2 ? 0x3BBC3BBCu : 0u, vm = r ? 0u : 0xC270C270u;
        const uint32_t vk = ((EMU_MASK >> kg) & 1) ? ve : vm;
#pragma unroll
        for (int i = 0; i < 4; i++) {
          const uint32_t v = i == 0 ? vq : i == 1 ? vk : i == 2 ? vv : 0u;
          uint8_t* q = pp + (i < 3 ? i * SEC_STRIDE : sizeof(G->qkv[0]));
          mbar_wait_c(BAR(B_E + 3 + i));
          *(uint4*)q = make_uint4(v, v, v, v);
          if (gs == 3) *(uint4*)(q + 16384) = make_uint4(v, v, v, v);
        }
        warp_arrive(BAR(B_PAD));
      }
#pragma unroll 1
      for (int ps = (wg + 1) & 3; ps < np; ps += 4) {
        float acc[64];
        const uint32_t fb = BAR(B_F) + 56 * ps;
        const uint64_t tw = (spare || ps < 3) ? (w ? T_W0 : T_W1) : ps == 3 ? T_W3 : reg ? T_W4 : T_W4Q, tx = (reg && ps >= 3) ? T_XB : T_X;
        const int br = p_br(ps), box = p_box(ps), sec = box >= 14 ? 2 : box >= 7 ? 1 : 0;
        const bool staged = ps >= 3 && !spare;
        uint32_t ad[4];
        {
          const int j = box - 7 * sec;
          const uint32_t lo = g * 64 + (j4 ^ (g >> 1)) * 16;
          const uint32_t base = staged ? S_STG + w * 20480 : br * sizeof(G->qkv[0]) + p_m(ps) * M_STRIDE + sec * SEC_STRIDE + 9 * j * 2048;
#pragma unroll
          for (int hf = 0; hf < 2; hf++) {
            const int i = 2 * ww + hf, t = i + j;
            const bool sh = t == 3 || t == 10;
            const uint32_t m0 = base + (i + (t >= 7 && !staged)) * 2048, m1 = !sh ? m0 : staged ? base + (i == 7 ? 9 : 8) * 2048 : m0 + 8192;
            ad[hf] = (g >= 4 ? m1 : m0) + lo;
            ad[2 + hf] = sh ? (g >= 4 ? m0 : m1) + lo : 0u;
          }
          pin<4>(ad);
        }
        const bool follow = !reg && ps == 1;
        mbar_wait_c(fb);
        if (ps == 1 && reg) mbar_wait_c(BAR(B_E));
        else if (ps > 1) {
          if (ps == 2) { mbar_wait_c(BAR(B_F + 5)); mbar_wait_c(BAR(B_F + 6)); }
          mbar_wait_c(fb - 16); mbar_wait_c(fb - 8);
          mbar_wait_c(fb + 8 * (B_E - B_F - 7 + 4));
        }
#pragma unroll
        for (int kc = 0; kc < 7; kc++) {
          const uint32_t da = (slot(tw, kc) >> 4) | L_W, db = (slot(tx, kc) >> 4) | L_X;
          if (kc) mbar_wait_c(fb + 8 * kc);
          if (follow || (kc < 2 && ps == 1)) mbar_wait_c(BAR(B_F + kc));
          if (kc == 2 && ps == 1 && reg) { mbar_wait_c(BAR(B_F + 5)); mbar_wait_c(BAR(B_F + 6)); mbar_wait_c(BAR(B_E + 4)); }
          wg_fence();
          if (kc == 0) wg128_ss_ta_z<H_SW, H_SW>(acc, da, db);
          else wg128_ss_ta<H_SW, H_SW>(acc, da, db);
#pragma unroll
          for (int k = 1; k < 4; k++) wg128_ss_ta<H_SW, H_SW>(acc, da + 128 * k, db + 2 * k);
          wg_commit();
          if (kc > 0) { wg_wait<1>(); if (l0) mbar_arrive(fb + 8 * (B_E - B_F + kc - 1)); }
        }
        wg_wait<0>();
        pin<64>(acc);
        if (l0) mbar_arrive(fb + 8 * (B_E - B_F + 6));
        uint32_t pk[32];
        if (br == 1 && sec < 2) {
#pragma unroll
          for (int i = 0; i < 32; i++) pk[i] = phi2(acc[2 * i], acc[2 * i + 1]);
        } else if (sec) {
#pragma unroll
          for (int i = 0; i < 32; i++) pk[i] = pack(acc[2 * i], acc[2 * i + 1]);
        } else {
#pragma unroll
          for (int i = 0; i < 32; i++) pk[i] = pack(acc[2 * i] * QSCALE, acc[2 * i + 1] * QSCALE);
        }
        pin<32>(pk);
        if (staged) {
          mbar_wait_c(BAR(B_E + 28 + 3) + 24 * w);
          const uint32_t pv = (sec == 2 && (g & 3) == 0) ? 0x3F803F80u : 0u;
#pragma unroll
          for (int hf = 0; hf < 2; hf++)
#pragma unroll
            for (int a = 0; a < 4; a++) sts128(ad[hf] + a * 512, pk[8 * a + hf], pk[8 * a + 2 + hf], pk[8 * a + 4 + hf], pk[8 * a + 6 + hf]);
          if (__any_sync(~0u, ad[2] | ad[3])) {
#pragma unroll 1
            for (int a = 0; a < 4; a++) sts128((ad[2] | ad[3]) + a * 512, pv, pv, pv, pv);
          }
        } else {
#pragma unroll
          for (int a = 0; a < 4; a++)
#pragma unroll
            for (int hf = 0; hf < 2; hf++)
              *(uint4*)(G->qkv[0] + ad[hf] + a * 512) = make_uint4(pk[8 * a + hf], pk[8 * a + 2 + hf], pk[8 * a + 4 + hf], pk[8 * a + 6 + hf]);
        }
        warp_arrive(BAR(B_SG) + 8 * ps);
        if (reg && ps < 2) {
          const unsigned ep = ld_epoch(G, bid);
          if (ps == 1) mbar_wait_c(BAR(B_SG + 2));
          const bool b2 = lane & 4, b3 = lane & 8;
#pragma unroll
          for (int i = 0; i < 32; i++) pk[i] = hsq(pk[i], 0);
#pragma unroll
          for (int i = 0; i < 32; i++)
            if (!(i & 4)) pk[i] = hadd(b2 ? pk[i + 4] : pk[i], __shfl_xor_sync(~0u, b2 ? pk[i] : pk[i + 4], 4));
#pragma unroll
          for (int i = 0; i < 32; i++)
            if (!(i & 6)) pk[i] = hadd(b3 ? pk[i + 2] : pk[i], __shfl_xor_sync(~0u, b3 ? pk[i] : pk[i + 2], 8));
          uint32_t mx[2] = {0, 0};
#pragma unroll
          for (int i = 0; i < 32; i++)
            if (!(i & 6)) {
              const uint32_t y = hadd(pk[i], __shfl_xor_sync(~0u, pk[i], 16));
              mx[i & 1] = __vmaxu2(mx[i & 1], ad[2 + (i & 1)] ? pk[i] : y);
            }
#pragma unroll
          for (int hf = 0; hf < 2; hf++) {
            mx[hf] = max(mx[hf] << 16, mx[hf] & 0xFFFF0000u) & 0x7FFFFFFFu;
            const uint32_t r0 = __reduce_max_sync(~0u, lane < 16 ? mx[hf] : 0u), r1 = __reduce_max_sync(~0u, lane < 16 ? 0u : mx[hf]);
            if ((lane & 15) == 0)
              asm volatile("st.relaxed.gpu.global.v2.u32 [%0], {%1, %2};" ::"l"(&G->nrm[ps][gm][(ad[hf] >> 11) & 63]), "r"(lane ? r1 : r0), "r"(ep) : "memory");
          }
        }
      }
    }
    if (!spare) {
      asm volatile("setmaxnreg.inc.sync.aligned.u32 112;");
      const uint32_t qoff = pair * 8192 + w * 1024;
      uint32_t unsafe = 0;
      int osrc = (lane & 28) | (hb ? 0 : 2);
      uint32_t ost = S_Q + qoff + (lane >> 4) * 2048 + (lane & 7) * 128 + (((2 * ww + ((lane >> 3) & 1)) ^ (lane & 7)) << 4);
      uint32_t odst = offsetof(Scratch, o) + (qb * 4 + wg) * 57344 + 7 * (h >> 1) * 1024;
      asm volatile("" : "+r"(osrc), "+r"(ost), "+r"(odst));
      float o[16];
      {
        float s[64];
        uint32_t p[32];
#pragma unroll
        for (int i = 0; i < 16; i++) o[i] = 0.f;
        pin<16>(o);
        const uint32_t dq = ((S_Q + qoff) >> 4) | L_T;
        uint32_t kb = BAR(B_KF);
        mbar_wait_c(BAR(B_QF));
        if (pair) mbar_wait_c(BAR(B_QF + 1));
#pragma unroll 1
        for (int seg = 0; seg < 4; seg++) {
#pragma unroll
          for (int u = 0; u < 4; u++) {
            const uint32_t kd = (ring_slot(u) >> 4) | L_T, vd = kd + 512;
            wg_fence();
            wg128_ss_ta_tb_z<H_T, H_T>(s, dq, kd);
            wg128_ss_ta_tb<H_T, H_T>(s, dq + 256, kd + 256);
            wg_commit();
            mbar_wait_c(kb + 8 * u);
            wg_wait<0>();
            pin<64>(s);
            if (l0) mbar_arrive(kb + 8 * (B_KE - B_KF + u));
#pragma unroll
            for (int g = 0; g < 16; g++) {
              if ((EMU_MASK >> g) & 1) {
                p[2 * g] = exp2_pair(s[4 * g], s[4 * g + 1]);
                p[2 * g + 1] = exp2_pair(s[4 * g + 2], s[4 * g + 3]);
              } else {
                p[2 * g] = pack(ex2(s[4 * g]), ex2(s[4 * g + 1]));
                p[2 * g + 1] = pack(ex2(s[4 * g + 2]), ex2(s[4 * g + 3]));
              }
            }
            pin<32>(p);
            wg_fence();
#pragma unroll
            for (int k = 0; k < 8; k++) wg32_rs<H_T>(o, p[4 * k], p[4 * k + 1], p[4 * k + 2], p[4 * k + 3], vd + 32 * (k >> 1) + 2 * (k & 1));
            wg_commit();
            wg_wait<0>();
            pin<16>(o);
            if (u == (T_OB & 3) && seg == (T_OB >> 2)) {
              mbar_wait_c(BAR(B_OBGO));
              const uint32_t a = dq + ((S_PQ >> 4) - (S_Q >> 4));
              constexpr uint32_t b = (S_KVM >> 4) | L_KV;
              wg_fence();
              wg32_ss_ta_tb_z<H_T, H_KV>(s, a, b);
              wg32_ss_ta_tb<H_T, H_KV>(s, a + 256, b + 64);
              wg_commit();
              unsafe = lds(S_MISC);
              wg_wait<0>();
              pin<16>(s);
              stage_o(s, 1e-6f, ost + (S_PKV - S_Q), osrc, 0);
              warp_arrive(BAR(B_SOB));
            }
            if (u == (T_KV & 3) && seg == (T_KV >> 2) && wg == 0) {
              mbar_wait_c(BAR(B_PKV));
              constexpr uint32_t a = (S_PKV >> 4) | L_T;
              wg_fence();
              wg32_ss_z<H_T, H_T>(s, a, a + 512);
#pragma unroll
              for (int k = 1; k < 16; k++)
                wg32_ss<H_T, H_T>(s, a + (k >> 3) * 1024 + (k & 6) * 16 + (k & 1) * 2, a + 512 + (k >> 3) * 1024 + (k & 6) * 16 + (k & 1) * 2);
              wg_commit();
              wg_wait<0>();
              pin<16>(s);
              if (ww < 2) {
                float2* dst = (float2*)G->part + L * 512 + ww * 256 + lane;
#pragma unroll
                for (int c = 0; c < 4; c++) {
                  dst[c * 32] = make_float2(s[4 * c], s[4 * c + 1]);
                  dst[128 + c * 32] = make_float2(s[4 * c + 2], s[4 * c + 3]);
                }
              }
              warp_arrive(BAR(B_SKV));
            }
          }
          kb += 32;
        }
      }
      uint32_t rank = 0;
      if ((tid & 127) == 32) asm volatile("atom.shared.inc.u32 %0, [%1], 7;" : "=r"(rank) : "r"(S_MISC + 4) : "memory");
      const uint32_t qdead = wg < 3 ? BAR(B_QD) + 8 * wg : BAR(B_QD3);
      if (l0) { mbar_arrive(qdead); mbar_arrive(BAR(B_KE + 16)); }
      {
        float a0 = 0.f, a1 = 0.f;
#pragma unroll
        for (int c = 0; c < 2; c++) {
          a0 = fmaxf(a0, fmaxf(fabsf(o[4 * c]), fabsf(o[4 * c + 1])));
          a1 = fmaxf(a1, fmaxf(fabsf(o[4 * c + 2]), fabsf(o[4 * c + 3])));
        }
        const bool bad = unsafe != 0 || fminf(a0, a1) < 7.888609e-31f;
        if (__any_sync(~0u, bad))
          attn_safe(o, G->qkv[0] + h * 8192 + (2 * qb + pair) * M_STRIDE, w * 8 + ww * 2, G->qkv[0] + h * 8192 + SEC_STRIDE, hb, lane);
      }
      stage_o(o, 0.f, ost, osrc, qdead);
      if ((tid & 127) == 32) asm volatile("st.shared.u32 [%0], %1;" ::"r"(S_MISC + 16 + 4 * wg), "r"(rank) : "memory");
      odst = __shfl_sync(~0u, odst, 0);
      wg_bar(wg);
      if (ww == 0 && elect()) {
        flush_o((uint8_t*)G + odst, S_Q + qoff, hb);
        mbar_arrive(BAR(B_OGO));
        bump(&G->cnt[(C_OA + qb * 4 + wg) * 32]);
        bulk_st_wait();
        mbar_arrive(BAR(B_QFREE));
      }
      __syncwarp();
      if (reg) {
        const int role = __shfl_sync(~0u, lds(S_MISC + 16 + 4 * wg), 0), pair = role >> 1, w = role & 1;
        float acc[32];
        mbar_wait_c(pair ? BAR(B_WOA) : BAR(B_WOB));
        mbar_wait_c(BAR(B_KE + 16));
        const uint32_t fb = BAR(B_OF) + 8 * (pair ? 7 + 7 * w : 0), eb = BAR(B_OE) + 56 * w;
        const bool rel = !pair && l0;
        uint8_t* dst = out + ((m64 + 2 * w) * 64 + (ww >> 1) * 32 + (ww & 1) * 4 + (lane >> 4) * 8 + ((lane >> 3) & 1)) * 1792
                       + (pair ? 0 : 896) + qb * 128 + (lane & 7) * 16;
        asm volatile("" : "+l"(dst));
#pragma unroll 1
        for (int attempt = 0;; attempt++) {
#pragma unroll
          for (int kc = 0; kc < 7; kc++) {
            const uint32_t a = ((pair ? (w ? oa_slot(kc, 1) : oa_slot(kc, 0)) : (w ? ob_slot(kc, 1) : ob_slot(kc, 0))) >> 4) | L_W;
            const uint32_t b = ((pair ? woa_slot(kc) : S_WOB + kc * 8192) >> 4) | L_W;
            mbar_wait_c(fb + 8 * kc);
            if (kc == 4 && pair) mbar_wait_c(BAR(B_WOA2));
            if (kc == 6 && pair) { mbar_wait_c(BAR(B_OE + 6)); mbar_wait_c(BAR(B_OE + 13)); }
            if (kc == 0 && role == 3) mbar_wait_c(BAR(B_ASEQ));
            wg_fence();
            if (kc == 0) wg64_ss_ta_tb_z<H_SW, H_SW>(acc, a, b);
            else wg64_ss_ta_tb<H_SW, H_SW>(acc, a, b);
#pragma unroll
            for (int k = 1; k < 4; k++) wg64_ss_ta_tb<H_SW, H_SW>(acc, a + 128 * k, b + 128 * k);
            wg_commit();
            if (kc == 5 && role == 2 && l0 && !attempt) mbar_arrive(BAR(B_ASEQ));
            if (kc > 0) { wg_wait<1>(); if (rel) mbar_arrive(eb + 8 * (kc - 1)); }
          }
          wg_wait<0>();
          pin<32>(acc);
          if (rel) mbar_arrive(eb + 8 * 6);
          if (!pair) { mbar_wait_c(BAR(B_OE + 6)); mbar_wait_c(BAR(B_OE + 13)); }
          if (l0 && !attempt) mbar_arrive(BAR(B_DONE));
          const bool nan = acc[0] != acc[0] || acc[2] != acc[2];
          const uint32_t st = S_WOB + 24576 + warp * 2048;
#pragma unroll
          for (int b = 0; b < 4; b++)
            asm volatile("stmatrix.sync.aligned.m8n8.x4.shared.b16 [%0], {%1,%2,%3,%4};"
                         ::"r"(st + (lane & 15) * 128 + (((2 * b + (lane >> 4)) ^ (lane & 7)) << 4)), "r"(pack(acc[8 * b], acc[8 * b + 1])),
                         "r"(pack(acc[8 * b + 2], acc[8 * b + 3])), "r"(pack(acc[8 * b + 4], acc[8 * b + 5])), "r"(pack(acc[8 * b + 6], acc[8 * b + 7])) : "memory");
          __syncwarp();
          uint4 v[4];
#pragma unroll
          for (int i = 0; i < 4; i++) {
            const int r = i * 4 + (lane >> 3);
            asm volatile("ld.shared.v4.u32 {%0,%1,%2,%3}, [%4];" : "=r"(v[i].x), "=r"(v[i].y), "=r"(v[i].z), "=r"(v[i].w) : "r"(st + r * 128 + (((lane ^ r) & 7) << 4)) : "memory");
          }
#pragma unroll
          for (int i = 0; i < 4; i++) {
            if (role < 3) { mbar_wait_c(BAR(B_OF + 7 + 2 * i)); mbar_wait_c(BAR(B_OF + 14 + 2 * i)); }
            *(uint4*)(dst + ((i & 1) * 16 + (i >> 1) * 2) * 1792) = v[i];
          }
          if (!pair || attempt) break;
          uint32_t redo;
          asm volatile("{\n.reg .pred p, q;\nsetp.ne.u32 p, %1, 0;\nbar.red.or.pred q, %2, 128, p;\nselp.u32 %0, 1, 0, q;\n}\n" : "=r"(redo) : "r"((uint32_t)nan), "r"(1 + wg) : "memory");
          if (!__shfl_sync(~0u, redo, 0)) break;
#pragma unroll 1
          for (int i = 0; i < 28; i++) {
            const int kc = i >> 2;
            const uint32_t off = (i & 3) * 2048 + (tid & 127) * 16;
            const uint8_t* src = G->o[0] + (m64 + 2 * w) * 57344 + kc * 8192 + off;
            uint4 x;
            for (int n = 0;; n++) {
              asm volatile("ld.relaxed.gpu.global.v4.u32 {%0,%1,%2,%3}, [%4];" : "=r"(x.x), "=r"(x.y), "=r"(x.z), "=r"(x.w) : "l"(src) : "memory");
              if (!__any_sync(~0u, x.x == ~0u || x.y == ~0u || x.z == ~0u || x.w == ~0u)) break;
              if (n > (1 << 22)) __trap();
            }
            const uint32_t sl = kc == 0 ? (w ? S_Q : oa_slot(0, 0)) : kc < 3 ? S_EXT + (kc - 1) * 16384 : kc == 3 ? S_R0 : kc == 4 ? S_R1 : kc == 5 ? S_R2 : oa_slot(6, 0);
            sts128(sl + w * 8192 + off, x.x, x.y, x.z, x.w);
          }
          async_fence();
          wg_bar(wg);
        }
      } else {
        if (l0) mbar_arrive(BAR(B_DONE));
      }
    }
  }
}

typedef CUresult (*EncodeFn)(CUtensorMap*, CUtensorMapDataType, cuuint32_t, void*, const cuuint64_t*, const cuuint64_t*,
                             const cuuint32_t*, const cuuint32_t*, CUtensorMapInterleave, CUtensorMapSwizzle,
                             CUtensorMapL2promotion, CUtensorMapFloatOOBfill);
void make_map(EncodeFn f, CUtensorMap* m, void* p, uint64_t cols, uint64_t rows, uint32_t box_rows) {
  cuuint64_t gd[2] = {cols, rows}, gs[1] = {cols * 2};
  cuuint32_t bd[2] = {64, box_rows}, es[2] = {1, 1};
  f(m, CU_TENSOR_MAP_DATA_TYPE_BFLOAT16, 2, p, gd, gs, bd, es, CU_TENSOR_MAP_INTERLEAVE_NONE, CU_TENSOR_MAP_SWIZZLE_128B,
    CU_TENSOR_MAP_L2_PROMOTION_NONE, CU_TENSOR_MAP_FLOAT_OOB_FILL_NONE);
}

}

extern "C" void kernel_launch(void* const* d_in, const int* in_sizes, int n_in, void* d_out, int out_size) {
  static EncodeFn enc = nullptr;
  static Scratch* scratch = nullptr;
  if (!enc) {
    void* fn = nullptr;
    cudaDriverEntryPointQueryResult q;
    cudaGetDriverEntryPoint("cuTensorMapEncodeTiled", &fn, cudaEnableDefault, &q);
    enc = (EncodeFn)fn;
    cudaGetSymbolAddress((void**)&scratch, gScratch);
    cudaFuncSetAttribute(fused_kernel, cudaFuncAttributeMaxDynamicSharedMemorySize, SMEM_BYTES);
  }
  Params P;
  for (int b = 0; b < 2; b++) {
    make_map(enc, &P.x[b], d_in[3 * b], 448, 2048, 128);
    make_map(enc, &P.w[b], d_in[3 * b + 1], 1344, 448, 64);
    make_map(enc, &P.wo[b], d_in[3 * b + 2], 448, 448, 64);
  }
  fused_kernel<<<NCTA, NTHREADS, SMEM_BYTES>>>(scratch, (uint8_t*)d_out, (const uint8_t*)d_in[0], (const uint8_t*)d_in[1], P);
}
```
